```python
import torch

def _softmax(x, axis=-1):
    return torch.softmax(x, dim=axis)

def _gelu(x):
    return torch.nn.functional.gelu(x, approximate='tanh')

def _silu(x):
    return torch.nn.functional.silu(x)

def _sigmoid(x):
    return torch.sigmoid(x)

def _layernorm(x, axis=-1, eps=1e-05):
    m = x.mean(dim=axis, keepdim=True)
    v = x.var(dim=axis, keepdim=True, unbiased=False)
    return (x - m) / torch.sqrt(v + eps)

def _scatter_add(tgt, idx, src, axis=0):
    return tgt.clone().index_add_(axis, idx, src)

def _segment_sum(src, seg, n):
    out = torch.zeros((n,) + src.shape[1:], dtype=src.dtype)
    return out.index_add_(0, seg, src)

def _pad(x, pw):
    flat = tuple((v for pair in reversed(pw) for v in pair))
    return torch.nn.functional.pad(x, flat)
kernel_name = 'adaLN_cond__spectral_fnet__dense_activation_relu__prompt'

def setup_inputs():

    _w = lambda a: (lambda t: t.to(torch.bfloat16) if t.is_floating_point() else t)(torch.as_tensor(a))

    def _A_setup():
        B, S, D = (1, 2048, 512)
        ns = torch.arange(S)[:, None] * torch.arange(S)[None, :]
        nd = torch.arange(D)[:, None] * torch.arange(D)[None, :]
        Ws_re = torch.cos(-2.0 * torch.pi * ns / S).to(float)
        Ws_im = torch.sin(-2.0 * torch.pi * ns / S).to(float)
        Wd_re = torch.cos(-2.0 * torch.pi * nd / D).to(float)
        Wd_im = torch.sin(-2.0 * torch.pi * nd / D).to(float)
        return {'x': _w((lambda *s: torch.randn(*s, dtype=torch.bfloat16) * 0.1)(B, S, D)), 'dft_seq_re': _w(Ws_re), 'dft_seq_im': _w(Ws_im), 'dft_hid_re': _w(Wd_re), 'dft_hid_im': _w(Wd_im)}
    _A_in = _A_setup()

    def _B_setup():
        B, S, D, Dff = (1, 2048, 512, 1376)
        return {'x': _w((lambda *s: torch.randn(*s, dtype=torch.bfloat16) * 0.1)(B, S, D)), 'w1': _w((lambda *s: torch.randn(*s, dtype=torch.bfloat16) * 3.2)(D, Dff)), 'w2': _w((lambda *s: torch.randn(*s, dtype=torch.bfloat16) * 3.2)(Dff, D))}
    _B_in = _B_setup()
    return {'A_x': _A_in['x'], 'A_dft_seq_re': _A_in['dft_seq_re'], 'A_dft_seq_im': _A_in['dft_seq_im'], 'A_dft_hid_re': _A_in['dft_hid_re'], 'A_dft_hid_im': _A_in['dft_hid_im'], 'B_x': _B_in['x'], 'B_w1': _B_in['w1'], 'B_w2': _B_in['w2'], 'c': _w((lambda *s: torch.randn(*s, dtype=torch.bfloat16) * 0.2)(1, 512) * 8.0), 'w_mod': _w((lambda *s: torch.randn(*s, dtype=torch.bfloat16) * 0.2)(512, 6 * 512) * 512 ** (-0.5) * 8.0)}

def reference(A_x, A_dft_seq_re, A_dft_seq_im, A_dft_hid_re, A_dft_hid_im, B_x, B_w1, B_w2, c, w_mod):

    def _A_ref(x, dft_seq_re, dft_seq_im, dft_hid_re, dft_hid_im):
        a = torch.einsum('bsd,ed->bse', x, dft_hid_re)
        b = torch.einsum('bsd,ed->bse', x, dft_hid_im)
        y = torch.einsum('ts,bse->bte', dft_seq_re, a) - torch.einsum('ts,bse->bte', dft_seq_im, b)
        return y

    def _B_ref(x, w1, w2):
        h = torch.einsum('bsd,df->bsf', x, w1)
        zero = torch.zeros_like(h)
        h = torch.maximum(h, zero)
        return torch.einsum('bsf,fd->bsd', h, w2)
    x = A_x
    mod = (_silu(c) @ w_mod).reshape(c.shape[0], 6, 1, -1)
    sa, ca, ga, sb, cb, gb = (mod[:, 0].clone(), mod[:, 1].clone(), mod[:, 2].clone(), mod[:, 3].clone(), mod[:, 4].clone(), mod[:, 5].clone())
    h = _layernorm(x, axis=-1) * (1 + ca) + sa
    x = x + ga * _A_ref(h, A_dft_seq_re, A_dft_seq_im, A_dft_hid_re, A_dft_hid_im)
    h = _layernorm(x, axis=-1) * (1 + cb) + sb
    x = x + gb * _B_ref(h, B_w1, B_w2)
    return x
```

```cpp
#include <cuda_runtime.h>
#include <cuda_bf16.h>
#include <cuda.h>
#include <stdint.h>

namespace {

constexpr int S_ = 2048;
constexpr int D_ = 512;
constexpr int DFF_ = 1376;

__device__ float g_mod[6 * D_];
__device__ __align__(1024) __nv_bfloat16 g_ab[S_ * 1024];
__device__ __align__(1024) float g_part[4 * S_ * D_];
__device__ __align__(1024) __nv_bfloat16 g_x1[S_ * D_];
__device__ __align__(1024) __nv_bfloat16 g_h1[S_ * DFF_];

__device__ __forceinline__ uint32_t smem_u32(const void* p) { return (uint32_t)__cvta_generic_to_shared(p); }

__device__ __forceinline__ void mbar_init(uint32_t bar, uint32_t count) {
    asm volatile("mbarrier.init.shared::cta.b64 [%0], %1;" ::"r"(bar), "r"(count) : "memory");
}
__device__ __forceinline__ void mbar_expect_tx(uint32_t bar, uint32_t bytes) {
    asm volatile("mbarrier.arrive.expect_tx.shared::cta.b64 _, [%0], %1;" ::"r"(bar), "r"(bytes) : "memory");
}
__device__ __forceinline__ void mbar_arrive(uint32_t bar) {
    asm volatile("mbarrier.arrive.shared::cta.b64 _, [%0];" ::"r"(bar) : "memory");
}
__device__ __forceinline__ void mbar_arrive_remote(uint32_t bar, uint32_t cta) {
    asm volatile(
        "{\n.reg .b32 ra;\nmapa.shared::cluster.u32 ra, %0, %1;\n"
        "mbarrier.arrive.release.cluster.shared::cluster.b64 _, [ra];\n}\n" ::"r"(bar),
        "r"(cta)
        : "memory");
}
__device__ __forceinline__ void mbar_wait(uint32_t bar, uint32_t parity) {
    uint32_t ok;
    int it = 0;
    do {
        asm volatile(
            "{\n.reg .pred p;\nmbarrier.try_wait.parity.shared::cta.b64 p, [%1], %2;\nselp.u32 %0, 1, 0, p;\n}\n"
            : "=r"(ok)
            : "r"(bar), "r"(parity)
            : "memory");
        if (++it > (1 << 22)) __trap();
    } while (!ok);
}
__device__ __forceinline__ void mbar_wait_cluster(uint32_t bar, uint32_t parity) {
    uint32_t ok;
    int it = 0;
    do {
        asm volatile(
            "{\n.reg .pred p;\nmbarrier.try_wait.parity.acquire.cluster.shared::cta.b64 p, [%1], %2;\nselp.u32 %0, 1, 0, p;\n}\n"
            : "=r"(ok)
            : "r"(bar), "r"(parity)
            : "memory");
        if (++it > (1 << 22)) __trap();
    } while (!ok);
}
__device__ __forceinline__ void tma_load_2d(uint32_t dst, const CUtensorMap* map, int c0, int c1, uint32_t bar) {
    asm volatile(
        "cp.async.bulk.tensor.2d.shared::cluster.global.mbarrier::complete_tx::bytes [%0], [%1, {%3, %4}], [%2];" ::"r"(dst),
        "l"(map), "r"(bar), "r"(c0), "r"(c1)
        : "memory");
}
__device__ __forceinline__ void tma_load_2d_mc(uint32_t dst, const CUtensorMap* map, int c0, int c1, uint32_t bar,
                                               uint16_t mask) {
    asm volatile(
        "cp.async.bulk.tensor.2d.shared::cluster.global.mbarrier::complete_tx::bytes.multicast::cluster [%0], [%1, {%3, %4}], [%2], %5;" ::"r"(dst),
        "l"(map), "r"(bar), "r"(c0), "r"(c1), "h"(mask)
        : "memory");
}
__device__ __forceinline__ void prefetch_tmap(const CUtensorMap* map) {
    asm volatile("prefetch.tensormap [%0];" ::"l"(map) : "memory");
}
__device__ __forceinline__ void fence_proxy_async() { asm volatile("fence.proxy.async.shared::cta;" ::: "memory"); }
__device__ __forceinline__ void fence_mbar_init() { asm volatile("fence.mbarrier_init.release.cluster;" ::: "memory"); }
__device__ __forceinline__ void cluster_sync() {
    asm volatile("barrier.cluster.arrive.release.aligned;\nbarrier.cluster.wait.acquire.aligned;" ::: "memory");
}
__device__ __forceinline__ uint32_t cluster_ctarank() {
    uint32_t r;
    asm volatile("mov.u32 %0, %%cluster_ctarank;" : "=r"(r));
    return r;
}
__device__ __forceinline__ void named_bar_sync(int id, int nthreads) {
    asm volatile("bar.sync %0, %1;" ::"r"(id), "r"(nthreads) : "memory");
}
__device__ __forceinline__ void wgmma_fence() { asm volatile("wgmma.fence.sync.aligned;" ::: "memory"); }
__device__ __forceinline__ void wgmma_commit() { asm volatile("wgmma.commit_group.sync.aligned;" ::: "memory"); }
template <int N>
__device__ __forceinline__ void wgmma_wait() {
    asm volatile("wgmma.wait_group.sync.aligned %0;" ::"n"(N) : "memory");
}
__device__ __forceinline__ uint64_t make_desc(uint32_t addr, uint32_t lbo_bytes, uint32_t sbo_bytes) {
    return (uint64_t)((addr & 0x3FFFF) >> 4) | ((uint64_t)(lbo_bytes >> 4) << 16) | ((uint64_t)(sbo_bytes >> 4) << 32) |
           (1ull << 62);
}

template <int TB>
__device__ __forceinline__ void wgmma_n64(float (&d)[32], uint64_t da, uint64_t db, int scale_d) {
    asm volatile(
        "{\n.reg .pred p;\nsetp.ne.b32 p, %34, 0;\n"
        "wgmma.mma_async.sync.aligned.m64n64k16.f32.bf16.bf16 "
        "{%0, %1, %2, %3, %4, %5, %6, %7, %8, %9, %10, %11, %12, %13, %14, %15, %16, %17, %18, %19, %20, %21, %22, %23, %24, %25, %26, %27, %28, %29, %30, %31}, "
        "%32, %33, p, 1, 1, 0, %35;\n}\n"
        : "+f"(d[0]), "+f"(d[1]), "+f"(d[2]), "+f"(d[3]), "+f"(d[4]), "+f"(d[5]), "+f"(d[6]), "+f"(d[7]), "+f"(d[8]), "+f"(d[9]), "+f"(d[10]), "+f"(d[11]), "+f"(d[12]), "+f"(d[13]), "+f"(d[14]), "+f"(d[15]), "+f"(d[16]), "+f"(d[17]), "+f"(d[18]), "+f"(d[19]), "+f"(d[20]), "+f"(d[21]), "+f"(d[22]), "+f"(d[23]), "+f"(d[24]), "+f"(d[25]), "+f"(d[26]), "+f"(d[27]), "+f"(d[28]), "+f"(d[29]), "+f"(d[30]), "+f"(d[31])
        : "l"(da), "l"(db), "r"(scale_d), "n"(TB));
}

template <int TB>
__device__ __forceinline__ void wgmma_n128(float (&d)[64], uint64_t da, uint64_t db, int scale_d) {
    asm volatile(
        "{\n.reg .pred p;\nsetp.ne.b32 p, %66, 0;\n"
        "wgmma.mma_async.sync.aligned.m64n128k16.f32.bf16.bf16 "
        "{%0, %1, %2, %3, %4, %5, %6, %7, %8, %9, %10, %11, %12, %13, %14, %15, %16, %17, %18, %19, %20, %21, %22, %23, %24, %25, %26, %27, %28, %29, %30, %31, %32, %33, %34, %35, %36, %37, %38, %39, %40, %41, %42, %43, %44, %45, %46, %47, %48, %49, %50, %51, %52, %53, %54, %55, %56, %57, %58, %59, %60, %61, %62, %63}, "
        "%64, %65, p, 1, 1, 0, %67;\n}\n"
        : "+f"(d[0]), "+f"(d[1]), "+f"(d[2]), "+f"(d[3]), "+f"(d[4]), "+f"(d[5]), "+f"(d[6]), "+f"(d[7]), "+f"(d[8]), "+f"(d[9]), "+f"(d[10]), "+f"(d[11]), "+f"(d[12]), "+f"(d[13]), "+f"(d[14]), "+f"(d[15]), "+f"(d[16]), "+f"(d[17]), "+f"(d[18]), "+f"(d[19]), "+f"(d[20]), "+f"(d[21]), "+f"(d[22]), "+f"(d[23]), "+f"(d[24]), "+f"(d[25]), "+f"(d[26]), "+f"(d[27]), "+f"(d[28]), "+f"(d[29]), "+f"(d[30]), "+f"(d[31]), "+f"(d[32]), "+f"(d[33]), "+f"(d[34]), "+f"(d[35]), "+f"(d[36]), "+f"(d[37]), "+f"(d[38]), "+f"(d[39]), "+f"(d[40]), "+f"(d[41]), "+f"(d[42]), "+f"(d[43]), "+f"(d[44]), "+f"(d[45]), "+f"(d[46]), "+f"(d[47]), "+f"(d[48]), "+f"(d[49]), "+f"(d[50]), "+f"(d[51]), "+f"(d[52]), "+f"(d[53]), "+f"(d[54]), "+f"(d[55]), "+f"(d[56]), "+f"(d[57]), "+f"(d[58]), "+f"(d[59]), "+f"(d[60]), "+f"(d[61]), "+f"(d[62]), "+f"(d[63])
        : "l"(da), "l"(db), "r"(scale_d), "n"(TB));
}

template <int TB>
__device__ __forceinline__ void wgmma_n176(float (&d)[88], uint64_t da, uint64_t db, int scale_d) {
    asm volatile(
        "{\n.reg .pred p;\nsetp.ne.b32 p, %90, 0;\n"
        "wgmma.mma_async.sync.aligned.m64n176k16.f32.bf16.bf16 "
        "{%0, %1, %2, %3, %4, %5, %6, %7, %8, %9, %10, %11, %12, %13, %14, %15, %16, %17, %18, %19, %20, %21, %22, %23, %24, %25, %26, %27, %28, %29, %30, %31, %32, %33, %34, %35, %36, %37, %38, %39, %40, %41, %42, %43, %44, %45, %46, %47, %48, %49, %50, %51, %52, %53, %54, %55, %56, %57, %58, %59, %60, %61, %62, %63, %64, %65, %66, %67, %68, %69, %70, %71, %72, %73, %74, %75, %76, %77, %78, %79, %80, %81, %82, %83, %84, %85, %86, %87}, "
        "%88, %89, p, 1, 1, 0, %91;\n}\n"
        : "+f"(d[0]), "+f"(d[1]), "+f"(d[2]), "+f"(d[3]), "+f"(d[4]), "+f"(d[5]), "+f"(d[6]), "+f"(d[7]), "+f"(d[8]), "+f"(d[9]), "+f"(d[10]), "+f"(d[11]), "+f"(d[12]), "+f"(d[13]), "+f"(d[14]), "+f"(d[15]), "+f"(d[16]), "+f"(d[17]), "+f"(d[18]), "+f"(d[19]), "+f"(d[20]), "+f"(d[21]), "+f"(d[22]), "+f"(d[23]), "+f"(d[24]), "+f"(d[25]), "+f"(d[26]), "+f"(d[27]), "+f"(d[28]), "+f"(d[29]), "+f"(d[30]), "+f"(d[31]), "+f"(d[32]), "+f"(d[33]), "+f"(d[34]), "+f"(d[35]), "+f"(d[36]), "+f"(d[37]), "+f"(d[38]), "+f"(d[39]), "+f"(d[40]), "+f"(d[41]), "+f"(d[42]), "+f"(d[43]), "+f"(d[44]), "+f"(d[45]), "+f"(d[46]), "+f"(d[47]), "+f"(d[48]), "+f"(d[49]), "+f"(d[50]), "+f"(d[51]), "+f"(d[52]), "+f"(d[53]), "+f"(d[54]), "+f"(d[55]), "+f"(d[56]), "+f"(d[57]), "+f"(d[58]), "+f"(d[59]), "+f"(d[60]), "+f"(d[61]), "+f"(d[62]), "+f"(d[63]), "+f"(d[64]), "+f"(d[65]), "+f"(d[66]), "+f"(d[67]), "+f"(d[68]), "+f"(d[69]), "+f"(d[70]), "+f"(d[71]), "+f"(d[72]), "+f"(d[73]), "+f"(d[74]), "+f"(d[75]), "+f"(d[76]), "+f"(d[77]), "+f"(d[78]), "+f"(d[79]), "+f"(d[80]), "+f"(d[81]), "+f"(d[82]), "+f"(d[83]), "+f"(d[84]), "+f"(d[85]), "+f"(d[86]), "+f"(d[87])
        : "l"(da), "l"(db), "r"(scale_d), "n"(TB));
}

template <int TB>
__device__ __forceinline__ void wgmma_n256(float (&d)[128], uint64_t da, uint64_t db, int scale_d) {
    asm volatile(
        "{\n.reg .pred p;\nsetp.ne.b32 p, %130, 0;\n"
        "wgmma.mma_async.sync.aligned.m64n256k16.f32.bf16.bf16 "
        "{%0, %1, %2, %3, %4, %5, %6, %7, %8, %9, %10, %11, %12, %13, %14, %15, %16, %17, %18, %19, %20, %21, %22, %23, %24, %25, %26, %27, %28, %29, %30, %31, %32, %33, %34, %35, %36, %37, %38, %39, %40, %41, %42, %43, %44, %45, %46, %47, %48, %49, %50, %51, %52, %53, %54, %55, %56, %57, %58, %59, %60, %61, %62, %63, %64, %65, %66, %67, %68, %69, %70, %71, %72, %73, %74, %75, %76, %77, %78, %79, %80, %81, %82, %83, %84, %85, %86, %87, %88, %89, %90, %91, %92, %93, %94, %95, %96, %97, %98, %99, %100, %101, %102, %103, %104, %105, %106, %107, %108, %109, %110, %111, %112, %113, %114, %115, %116, %117, %118, %119, %120, %121, %122, %123, %124, %125, %126, %127}, "
        "%128, %129, p, 1, 1, 0, %131;\n}\n"
        : "+f"(d[0]), "+f"(d[1]), "+f"(d[2]), "+f"(d[3]), "+f"(d[4]), "+f"(d[5]), "+f"(d[6]), "+f"(d[7]), "+f"(d[8]), "+f"(d[9]), "+f"(d[10]), "+f"(d[11]), "+f"(d[12]), "+f"(d[13]), "+f"(d[14]), "+f"(d[15]), "+f"(d[16]), "+f"(d[17]), "+f"(d[18]), "+f"(d[19]), "+f"(d[20]), "+f"(d[21]), "+f"(d[22]), "+f"(d[23]), "+f"(d[24]), "+f"(d[25]), "+f"(d[26]), "+f"(d[27]), "+f"(d[28]), "+f"(d[29]), "+f"(d[30]), "+f"(d[31]), "+f"(d[32]), "+f"(d[33]), "+f"(d[34]), "+f"(d[35]), "+f"(d[36]), "+f"(d[37]), "+f"(d[38]), "+f"(d[39]), "+f"(d[40]), "+f"(d[41]), "+f"(d[42]), "+f"(d[43]), "+f"(d[44]), "+f"(d[45]), "+f"(d[46]), "+f"(d[47]), "+f"(d[48]), "+f"(d[49]), "+f"(d[50]), "+f"(d[51]), "+f"(d[52]), "+f"(d[53]), "+f"(d[54]), "+f"(d[55]), "+f"(d[56]), "+f"(d[57]), "+f"(d[58]), "+f"(d[59]), "+f"(d[60]), "+f"(d[61]), "+f"(d[62]), "+f"(d[63]), "+f"(d[64]), "+f"(d[65]), "+f"(d[66]), "+f"(d[67]), "+f"(d[68]), "+f"(d[69]), "+f"(d[70]), "+f"(d[71]), "+f"(d[72]), "+f"(d[73]), "+f"(d[74]), "+f"(d[75]), "+f"(d[76]), "+f"(d[77]), "+f"(d[78]), "+f"(d[79]), "+f"(d[80]), "+f"(d[81]), "+f"(d[82]), "+f"(d[83]), "+f"(d[84]), "+f"(d[85]), "+f"(d[86]), "+f"(d[87]), "+f"(d[88]), "+f"(d[89]), "+f"(d[90]), "+f"(d[91]), "+f"(d[92]), "+f"(d[93]), "+f"(d[94]), "+f"(d[95]), "+f"(d[96]), "+f"(d[97]), "+f"(d[98]), "+f"(d[99]), "+f"(d[100]), "+f"(d[101]), "+f"(d[102]), "+f"(d[103]), "+f"(d[104]), "+f"(d[105]), "+f"(d[106]), "+f"(d[107]), "+f"(d[108]), "+f"(d[109]), "+f"(d[110]), "+f"(d[111]), "+f"(d[112]), "+f"(d[113]), "+f"(d[114]), "+f"(d[115]), "+f"(d[116]), "+f"(d[117]), "+f"(d[118]), "+f"(d[119]), "+f"(d[120]), "+f"(d[121]), "+f"(d[122]), "+f"(d[123]), "+f"(d[124]), "+f"(d[125]), "+f"(d[126]), "+f"(d[127])
        : "l"(da), "l"(db), "r"(scale_d), "n"(TB));
}


template <int BN, int TB>
__device__ __forceinline__ void wgmma_bn(float (&d)[BN / 2], uint64_t da, uint64_t db, int scale_d) {
    if constexpr (BN == 64) wgmma_n64<TB>(d, da, db, scale_d);
    else if constexpr (BN == 128) wgmma_n128<TB>(d, da, db, scale_d);
    else if constexpr (BN == 176) wgmma_n176<TB>(d, da, db, scale_d);
    else wgmma_n256<TB>(d, da, db, scale_d);
}

__device__ __forceinline__ uint32_t pack_bf16(float a, float b) {
    __nv_bfloat162 v = __floats2bfloat162_rn(a, b);
    return *reinterpret_cast<uint32_t*>(&v);
}

__global__ void __launch_bounds__(256) mod_kernel(const __nv_bfloat16* __restrict__ c,
                                                  const __nv_bfloat16* __restrict__ w_mod) {
    __shared__ float sc[D_];
    __shared__ float red[64][33];
    for (int i = threadIdx.x; i < D_; i += 256) {
        float v = __bfloat162float(c[i]);
        float s = v / (1.0f + __expf(-v));
        sc[i] = __bfloat162float(__float2bfloat16(s));
    }
    __syncthreads();
    const int chunk = threadIdx.x & 3, rg = threadIdx.x >> 2;
    const int col0 = blockIdx.x * 32 + chunk * 8;
    uint4 v[8];
#pragma unroll
    for (int r = 0; r < 8; r++) v[r] = *reinterpret_cast<const uint4*>(w_mod + (size_t)(rg * 8 + r) * (6 * D_) + col0);
    float acc[8];
#pragma unroll
    for (int j = 0; j < 8; j++) acc[j] = 0.f;
#pragma unroll
    for (int r = 0; r < 8; r++) {
        float s = sc[rg * 8 + r];
        const __nv_bfloat162* p = reinterpret_cast<const __nv_bfloat162*>(&v[r]);
#pragma unroll
        for (int j = 0; j < 4; j++) {
            float2 f = __bfloat1622float2(p[j]);
            acc[2 * j] += s * f.x;
            acc[2 * j + 1] += s * f.y;
        }
    }
#pragma unroll
    for (int j = 0; j < 8; j++) red[rg][chunk * 8 + j] = acc[j];
    __syncthreads();
    if (threadIdx.x < 32) {
        float s = 0.f;
#pragma unroll 8
        for (int r = 0; r < 64; r++) s += red[r][threadIdx.x];
        g_mod[blockIdx.x * 32 + threadIdx.x] = __bfloat162float(__float2bfloat16(s));
    }
}

__global__ void __launch_bounds__(256) combine_kernel(const __nv_bfloat16* __restrict__ x) {
    const int idx = (blockIdx.x * 256 + threadIdx.x) * 8;
    const int col = idx & (D_ - 1);
    float y[8];
#pragma unroll
    for (int h = 0; h < 2; h++) {
        float4 p0 = *reinterpret_cast<const float4*>(g_part + 0 * S_ * D_ + idx + h * 4);
        float4 p1 = *reinterpret_cast<const float4*>(g_part + 1 * S_ * D_ + idx + h * 4);
        float4 p2 = *reinterpret_cast<const float4*>(g_part + 2 * S_ * D_ + idx + h * 4);
        float4 p3 = *reinterpret_cast<const float4*>(g_part + 3 * S_ * D_ + idx + h * 4);
        y[h * 4 + 0] = (p0.x + p1.x) - (p2.x + p3.x);
        y[h * 4 + 1] = (p0.y + p1.y) - (p2.y + p3.y);
        y[h * 4 + 2] = (p0.z + p1.z) - (p2.z + p3.z);
        y[h * 4 + 3] = (p0.w + p1.w) - (p2.w + p3.w);
    }
    uint4 xv = *reinterpret_cast<const uint4*>(x + idx);
    const __nv_bfloat162* xp = reinterpret_cast<const __nv_bfloat162*>(&xv);
    uint4 o;
    uint32_t* op = reinterpret_cast<uint32_t*>(&o);
#pragma unroll
    for (int j = 0; j < 4; j++) {
        float2 f = __bfloat1622float2(xp[j]);
        float g0 = g_mod[2 * D_ + col + 2 * j], g1 = g_mod[2 * D_ + col + 2 * j + 1];
        op[j] = pack_bf16(f.x + g0 * y[2 * j], f.y + g1 * y[2 * j + 1]);
    }
    *reinterpret_cast<uint4*>(g_x1 + idx) = o;
}

template <int VAR>
struct Cfg;
template <>
struct Cfg<1> {
    static constexpr int BN = 128, STAGES = 5, KT = 8, CL = 1;
    static constexpr bool A_RES = true, B_MN = false;
    static constexpr int B_STAGE = 16384;
};
template <>
struct Cfg<2> {
    static constexpr int BN = 256, STAGES = 4, KT = 16, CL = 4;
    static constexpr bool A_RES = false, B_MN = true;
    static constexpr int B_STAGE = 32768;
};
template <>
struct Cfg<3> {
    static constexpr int BN = 176, STAGES = 4, KT = 8, CL = 1;
    static constexpr bool A_RES = true, B_MN = true;
    static constexpr int B_STAGE = 24576;
};
template <>
struct Cfg<4> {
    static constexpr int BN = 64, STAGES = 8, KT = 22, CL = 1;
    static constexpr bool A_RES = false, B_MN = true;
    static constexpr int B_STAGE = 8192;
};

template <int VAR>
constexpr int smem_bytes() {
    using C = Cfg<VAR>;
    return (C::A_RES ? 131072 : C::STAGES * 16384) + C::STAGES * C::B_STAGE + 1024 + 256;
}

template <int VAR>
__global__ void __launch_bounds__(288, 1)
    gemm_kernel(const __grid_constant__ CUtensorMap tmA0, const __grid_constant__ CUtensorMap tmA1,
                const __grid_constant__ CUtensorMap tmB0, const __grid_constant__ CUtensorMap tmB1,
                const __nv_bfloat16* __restrict__ xin, __nv_bfloat16* __restrict__ out) {
    using C = Cfg<VAR>;
    constexpr int BN = C::BN, STAGES = C::STAGES, KT = C::KT, CL = C::CL;
    constexpr int A_BYTES = C::A_RES ? 131072 : STAGES * 16384;
    extern __shared__ uint8_t smem_raw[];
    const uint32_t smem_base = (smem_u32(smem_raw) + 1023u) & ~1023u;
    const uint32_t sA = smem_base;
    const uint32_t sB = smem_base + A_BYTES;
    const uint32_t bars = sB + STAGES * C::B_STAGE;
    const uint32_t full0 = bars, empty0 = bars + 8 * STAGES;

    const int tid = threadIdx.x, warp = tid >> 5, lane = tid & 31;

    int mt, nt, kq = 0;
    uint32_t rank = 0;
    if constexpr (VAR == 2) {
        rank = cluster_ctarank();
        const int cid = blockIdx.x >> 2;
        kq = cid & 3;
        nt = (cid >> 2) & 1;
        mt = (cid >> 3) * 4 + (int)rank;
    } else {
        constexpr int NT = (VAR == 1) ? 8 : 8;
        mt = blockIdx.x / NT;
        nt = blockIdx.x % NT;
    }
    const int m0 = mt * 128;

    if (tid == 0) {
        for (int i = 0; i < STAGES; i++) {
            mbar_init(full0 + 8 * i, 1);
            mbar_init(empty0 + 8 * i, 2 * CL);
        }
        fence_mbar_init();
    }
    if constexpr (CL > 1) cluster_sync();
    else __syncthreads();

    if (warp == 8) {
        if (lane == 0) {
            prefetch_tmap(&tmA0);
            prefetch_tmap(&tmB0);
            int stage = 0, phase = 1;
            for (int kt = 0; kt < KT; kt++) {
                if constexpr (CL > 1) mbar_wait_cluster(empty0 + 8 * stage, phase);
                else mbar_wait(empty0 + 8 * stage, phase);
                const uint32_t fb = full0 + 8 * stage;
                mbar_expect_tx(fb, (C::A_RES ? 0 : 16384) + C::B_STAGE);
                if constexpr (VAR == 1) {
                    tma_load_2d(sB + stage * C::B_STAGE, nt < 4 ? &tmB0 : &tmB1, kt * 64, (nt & 3) * 128, fb);
                } else if constexpr (VAR == 2) {
                    const int k0 = (kq & 1) * 1024 + kt * 64;
                    tma_load_2d(sA + stage * 16384, kq < 2 ? &tmA0 : &tmA1, k0, m0, fb);
                    tma_load_2d_mc(sB + stage * C::B_STAGE + rank * 8192, &tmB0, (kq >> 1) * 512 + nt * 256 + rank * 64,
                                   k0, fb, (uint16_t)0xF);
                } else if constexpr (VAR == 3) {
#pragma unroll
                    for (int q = 0; q < 3; q++)
                        tma_load_2d(sB + stage * C::B_STAGE + q * 8192, &tmB0, nt * 176 + q * 64, kt * 64, fb);
                } else {
                    tma_load_2d(sA + stage * 16384, &tmA0, kt * 64, m0, fb);
                    tma_load_2d(sB + stage * C::B_STAGE, &tmB0, nt * 64, kt * 64, fb);
                }
                if (++stage == STAGES) {
                    stage = 0;
                    phase ^= 1;
                }
            }
        }
    } else {
        const int wg = warp >> 2;
        if constexpr (C::A_RES) {
            const __nv_bfloat16* src = (VAR == 1) ? xin : g_x1;
            const float* msh = g_mod + (VAR == 1 ? 0 : 3 * D_);
            const float* msc = g_mod + (VAR == 1 ? 1 * D_ : 4 * D_);
            uint4 v[16][2];
#pragma unroll
            for (int r = 0; r < 16; r++) {
                const __nv_bfloat16* row = src + (size_t)(m0 + warp * 16 + r) * D_;
                v[r][0] = *reinterpret_cast<const uint4*>(row + lane * 8);
                v[r][1] = *reinterpret_cast<const uint4*>(row + 256 + lane * 8);
            }
            float sh[16], sc[16];
#pragma unroll
            for (int j = 0; j < 8; j++) {
                sh[j] = msh[lane * 8 + j];
                sc[j] = 1.0f + msc[lane * 8 + j];
                sh[8 + j] = msh[256 + lane * 8 + j];
                sc[8 + j] = 1.0f + msc[256 + lane * 8 + j];
            }
#pragma unroll
            for (int r = 0; r < 16; r++) {
                float f[16];
                const __nv_bfloat162* p0 = reinterpret_cast<const __nv_bfloat162*>(&v[r][0]);
                const __nv_bfloat162* p1 = reinterpret_cast<const __nv_bfloat162*>(&v[r][1]);
#pragma unroll
                for (int j = 0; j < 4; j++) {
                    float2 a = __bfloat1622float2(p0[j]);
                    f[2 * j] = a.x;
                    f[2 * j + 1] = a.y;
                    float2 b = __bfloat1622float2(p1[j]);
                    f[8 + 2 * j] = b.x;
                    f[8 + 2 * j + 1] = b.y;
                }
                float s = 0.f;
#pragma unroll
                for (int j = 0; j < 16; j++) s += f[j];
#pragma unroll
                for (int o = 16; o > 0; o >>= 1) s += __shfl_xor_sync(0xffffffffu, s, o);
                const float mean = s * (1.0f / D_);
                float q = 0.f;
#pragma unroll
                for (int j = 0; j < 16; j++) {
                    f[j] -= mean;
                    q += f[j] * f[j];
                }
#pragma unroll
                for (int o = 16; o > 0; o >>= 1) q += __shfl_xor_sync(0xffffffffu, q, o);
                const float rstd = rsqrtf(q * (1.0f / D_) + 1e-5f);
                uint4 o0, o1;
                uint32_t* o0p = reinterpret_cast<uint32_t*>(&o0);
                uint32_t* o1p = reinterpret_cast<uint32_t*>(&o1);
#pragma unroll
                for (int j = 0; j < 4; j++) {
                    o0p[j] = pack_bf16(f[2 * j] * rstd * sc[2 * j] + sh[2 * j], f[2 * j + 1] * rstd * sc[2 * j + 1] + sh[2 * j + 1]);
                    o1p[j] = pack_bf16(f[8 + 2 * j] * rstd * sc[8 + 2 * j] + sh[8 + 2 * j],
                                       f[8 + 2 * j + 1] * rstd * sc[8 + 2 * j + 1] + sh[8 + 2 * j + 1]);
                }
                const int row = warp * 16 + r;
                const uint32_t chunk = (uint32_t)(lane & 7) ^ (uint32_t)(row & 7);
                const uint32_t a0 = sA + (lane >> 3) * 16384 + row * 128 + chunk * 16;
                const uint32_t a1 = a0 + 4 * 16384;
                asm volatile("st.shared.v4.b32 [%0], {%1, %2, %3, %4};" ::"r"(a0), "r"(o0.x), "r"(o0.y), "r"(o0.z), "r"(o0.w) : "memory");
                asm volatile("st.shared.v4.b32 [%0], {%1, %2, %3, %4};" ::"r"(a1), "r"(o1.x), "r"(o1.y), "r"(o1.z), "r"(o1.w) : "memory");
            }
            fence_proxy_async();
            named_bar_sync(1, 256);
        }

        float acc[BN / 2];
        int stage = 0, phase = 0;
        for (int kt = 0; kt < KT; kt++) {
            mbar_wait(full0 + 8 * stage, phase);
            const uint32_t a_base = (C::A_RES ? sA + kt * 16384 : sA + stage * 16384) + wg * 8192;
            const uint32_t b_base = sB + stage * C::B_STAGE;
            wgmma_fence();
#pragma unroll
            for (int k = 0; k < 4; k++) {
                const uint64_t da = make_desc(a_base + k * 32, 16, 1024);
                uint64_t db;
                if constexpr (C::B_MN) db = make_desc(b_base + k * 2048, 8192, 1024);
                else db = make_desc(b_base + k * 32, 16, 1024);
                wgmma_bn<BN, C::B_MN ? 1 : 0>(acc, da, db, (kt | k) != 0);
            }
            wgmma_commit();
            if (kt > 0) {
                wgmma_wait<1>();
                const int ps = (stage == 0) ? STAGES - 1 : stage - 1;
                if constexpr (CL > 1) {
                    if ((tid & 127) < CL) mbar_arrive_remote(empty0 + 8 * ps, tid & 127);
                } else {
                    if ((tid & 127) == 0) mbar_arrive(empty0 + 8 * ps);
                }
            }
            if (++stage == STAGES) {
                stage = 0;
                phase ^= 1;
            }
        }
        wgmma_wait<0>();

        const int r0 = wg * 64 + (warp & 3) * 16 + (lane >> 2);
        const int cq = (lane & 3) * 2;
        if constexpr (VAR == 2) {
            float* dst = g_part + (size_t)kq * S_ * D_ + (size_t)(m0 + r0) * D_ + nt * 256 + cq;
#pragma unroll
            for (int j = 0; j < BN / 8; j++) {
                *reinterpret_cast<float2*>(dst + j * 8) = make_float2(acc[4 * j], acc[4 * j + 1]);
                *reinterpret_cast<float2*>(dst + 8 * D_ + j * 8) = make_float2(acc[4 * j + 2], acc[4 * j + 3]);
            }
        } else {
            named_bar_sync(2, 256);
            const uint32_t stg = smem_base + wg * 32768;
            const int rl = (warp & 3) * 16 + (lane >> 2);
            if constexpr (VAR == 4) {
                const __nv_bfloat16* xr = g_x1 + (size_t)(m0 + r0) * D_ + nt * 64 + cq;
                const float* gb = g_mod + 5 * D_ + nt * 64 + cq;
#pragma unroll
                for (int j = 0; j < BN / 8; j++) {
                    float2 xa = __bfloat1622float2(*reinterpret_cast<const __nv_bfloat162*>(xr + j * 8));
                    float2 xb = __bfloat1622float2(*reinterpret_cast<const __nv_bfloat162*>(xr + 8 * D_ + j * 8));
                    float g0 = gb[j * 8], g1 = gb[j * 8 + 1];
                    acc[4 * j + 0] = xa.x + g0 * acc[4 * j + 0];
                    acc[4 * j + 1] = xa.y + g1 * acc[4 * j + 1];
                    acc[4 * j + 2] = xb.x + g0 * acc[4 * j + 2];
                    acc[4 * j + 3] = xb.y + g1 * acc[4 * j + 3];
                }
            }
#pragma unroll
            for (int j = 0; j < BN / 8; j++) {
                float v0 = acc[4 * j], v1 = acc[4 * j + 1], v2 = acc[4 * j + 2], v3 = acc[4 * j + 3];
                if constexpr (VAR == 3) {
                    v0 = fmaxf(v0, 0.f);
                    v1 = fmaxf(v1, 0.f);
                    v2 = fmaxf(v2, 0.f);
                    v3 = fmaxf(v3, 0.f);
                }
                const uint32_t sub = stg + (j >> 3) * 8192;
                const uint32_t ch = (uint32_t)(j & 7);
                const uint32_t ad0 = sub + rl * 128 + ((ch ^ (uint32_t)(rl & 7)) << 4) + cq * 2;
                const uint32_t ad1 = sub + (rl + 8) * 128 + ((ch ^ (uint32_t)((rl + 8) & 7)) << 4) + cq * 2;
                asm volatile("st.shared.b32 [%0], %1;" ::"r"(ad0), "r"(pack_bf16(v0, v1)) : "memory");
                asm volatile("st.shared.b32 [%0], %1;" ::"r"(ad1), "r"(pack_bf16(v2, v3)) : "memory");
            }
            named_bar_sync(3 + wg, 128);
            constexpr int NCH = BN / 8;
            const int t = tid & 127;
            for (int i = t; i < 64 * NCH; i += 128) {
                const int row = i / NCH, ch = i % NCH;
                const uint32_t ad = stg + (ch >> 3) * 8192 + row * 128 + ((((uint32_t)ch & 7) ^ (uint32_t)(row & 7)) << 4);
                uint4 val;
                asm volatile("ld.shared.v4.b32 {%0, %1, %2, %3}, [%4];" : "=r"(val.x), "=r"(val.y), "=r"(val.z), "=r"(val.w) : "r"(ad));
                const int grow = m0 + wg * 64 + row;
                if constexpr (VAR == 1) {
                    *reinterpret_cast<uint4*>(g_ab + (size_t)grow * 1024 + nt * 128 + ch * 8) = val;
                } else if constexpr (VAR == 3) {
                    const int gc = nt * 176 + ch * 8;
                    if (gc < DFF_) *reinterpret_cast<uint4*>(g_h1 + (size_t)grow * DFF_ + gc) = val;
                } else {
                    *reinterpret_cast<uint4*>(out + (size_t)grow * D_ + nt * 64 + ch * 8) = val;
                }
            }
        }
    }
    if constexpr (CL > 1) cluster_sync();
}

typedef CUresult (*EncodeFn)(CUtensorMap*, CUtensorMapDataType, cuuint32_t, void*, const cuuint64_t*, const cuuint64_t*,
                             const cuuint32_t*, const cuuint32_t*, CUtensorMapInterleave, CUtensorMapSwizzle,
                             CUtensorMapL2promotion, CUtensorMapFloatOOBfill);

void make_map(EncodeFn fn, CUtensorMap* m, const void* ptr, uint64_t inner, uint64_t outer, uint64_t pitch_bytes,
              uint32_t box_inner, uint32_t box_outer) {
    cuuint64_t dims[2] = {inner, outer};
    cuuint64_t strides[1] = {pitch_bytes};
    cuuint32_t box[2] = {box_inner, box_outer};
    cuuint32_t estr[2] = {1, 1};
    fn(m, CU_TENSOR_MAP_DATA_TYPE_BFLOAT16, 2, const_cast<void*>(ptr), dims, strides, box, estr,
       CU_TENSOR_MAP_INTERLEAVE_NONE, CU_TENSOR_MAP_SWIZZLE_128B, CU_TENSOR_MAP_L2_PROMOTION_L2_256B,
       CU_TENSOR_MAP_FLOAT_OOB_FILL_NONE);
}

template <int VAR>
void launch_gemm(int grid, const CUtensorMap& a0, const CUtensorMap& a1, const CUtensorMap& b0, const CUtensorMap& b1,
                 const __nv_bfloat16* xin, __nv_bfloat16* out, cudaStream_t st) {
    cudaLaunchConfig_t cfg = {};
    cfg.gridDim = dim3(grid);
    cfg.blockDim = dim3(288);
    cfg.dynamicSmemBytes = smem_bytes<VAR>();
    cfg.stream = st;
    cudaLaunchAttribute attr[1];
    attr[0].id = cudaLaunchAttributeClusterDimension;
    attr[0].val.clusterDim.x = Cfg<VAR>::CL;
    attr[0].val.clusterDim.y = 1;
    attr[0].val.clusterDim.z = 1;
    cfg.attrs = attr;
    cfg.numAttrs = 1;
    cudaLaunchKernelEx(&cfg, gemm_kernel<VAR>, a0, a1, b0, b1, xin, out);
}

}

extern "C" void kernel_launch(void* const* d_in, const int* in_sizes, int n_in, void* d_out, int out_size) {
    const __nv_bfloat16* x = (const __nv_bfloat16*)d_in[0];
    const __nv_bfloat16* ws_re = (const __nv_bfloat16*)d_in[1];
    const __nv_bfloat16* ws_im = (const __nv_bfloat16*)d_in[2];
    const __nv_bfloat16* wd_re = (const __nv_bfloat16*)d_in[3];
    const __nv_bfloat16* wd_im = (const __nv_bfloat16*)d_in[4];
    const __nv_bfloat16* w1 = (const __nv_bfloat16*)d_in[6];
    const __nv_bfloat16* w2 = (const __nv_bfloat16*)d_in[7];
    const __nv_bfloat16* c = (const __nv_bfloat16*)d_in[8];
    const __nv_bfloat16* w_mod = (const __nv_bfloat16*)d_in[9];
    __nv_bfloat16* out = (__nv_bfloat16*)d_out;
    cudaStream_t st = cudaStreamPerThread;

    static EncodeFn enc = nullptr;
    static bool attr_done = false;
    if (!enc) {
        void* fn = nullptr;
        cudaDriverEntryPointQueryResult qres;
        cudaGetDriverEntryPoint("cuTensorMapEncodeTiled", &fn, cudaEnableDefault, &qres);
        enc = (EncodeFn)fn;
    }
    if (!attr_done) {
        cudaFuncSetAttribute(gemm_kernel<1>, cudaFuncAttributeMaxDynamicSharedMemorySize, smem_bytes<1>());
        cudaFuncSetAttribute(gemm_kernel<2>, cudaFuncAttributeMaxDynamicSharedMemorySize, smem_bytes<2>());
        cudaFuncSetAttribute(gemm_kernel<3>, cudaFuncAttributeMaxDynamicSharedMemorySize, smem_bytes<3>());
        cudaFuncSetAttribute(gemm_kernel<4>, cudaFuncAttributeMaxDynamicSharedMemorySize, smem_bytes<4>());
        attr_done = true;
    }
    void *p_ab, *p_h1;
    cudaGetSymbolAddress(&p_ab, g_ab);
    cudaGetSymbolAddress(&p_h1, g_h1);

    CUtensorMap tm_wdre, tm_wdim, tm_wsre, tm_wsim, tm_ab, tm_w1, tm_h1, tm_w2;
    make_map(enc, &tm_wdre, wd_re, D_, D_, D_ * 2, 64, 128);
    make_map(enc, &tm_wdim, wd_im, D_, D_, D_ * 2, 64, 128);
    make_map(enc, &tm_wsre, ws_re, S_, S_, S_ * 2, 64, 128);
    make_map(enc, &tm_wsim, ws_im, S_, S_, S_ * 2, 64, 128);
    make_map(enc, &tm_ab, p_ab, 1024, S_, 1024 * 2, 64, 64);
    make_map(enc, &tm_w1, w1, DFF_, D_, DFF_ * 2, 64, 64);
    make_map(enc, &tm_h1, p_h1, DFF_, S_, DFF_ * 2, 64, 128);
    make_map(enc, &tm_w2, w2, D_, DFF_, D_ * 2, 64, 64);

    mod_kernel<<<96, 256, 0, st>>>(c, w_mod);
    launch_gemm<1>(128, tm_wdre, tm_wdre, tm_wdre, tm_wdim, x, nullptr, st);
    launch_gemm<2>(128, tm_wsre, tm_wsim, tm_ab, tm_ab, nullptr, nullptr, st);
    combine_kernel<<<S_ * D_ / (256 * 8), 256, 0, st>>>(x);
    launch_gemm<3>(128, tm_w1, tm_w1, tm_w1, tm_w1, nullptr, nullptr, st);
    launch_gemm<4>(128, tm_h1, tm_h1, tm_w2, tm_w2, nullptr, out, st);
}
```

```cpp
#include <cuda_runtime.h>
#include <cuda_bf16.h>
#include <cuda.h>
#include <stdint.h>

#define PDL_LN 0
namespace {

constexpr int S_ = 2048;
constexpr int D_ = 512;
constexpr int DFF_ = 1376;

__device__ float g_mod[6 * D_];
__device__ unsigned int g_mod_cnt;
__device__ unsigned int g_rb_cnt[16];
__device__ __align__(1024) __nv_bfloat16 g_ab[S_ * 1024];
__device__ __align__(1024) __nv_bfloat16 g_part[4 * S_ * D_];
__device__ __align__(1024) __nv_bfloat16 g_h2[S_ * D_];
__device__ __align__(1024) __nv_bfloat16 g_x1[S_ * D_];
__device__ __align__(1024) __nv_bfloat16 g_h1[S_ * DFF_];

__device__ __forceinline__ uint32_t smem_u32(const void* p) { return (uint32_t)__cvta_generic_to_shared(p); }

__device__ __forceinline__ void mbar_init(uint32_t bar, uint32_t count) {
    asm volatile("mbarrier.init.shared::cta.b64 [%0], %1;" ::"r"(bar), "r"(count) : "memory");
}
__device__ __forceinline__ void mbar_expect_tx(uint32_t bar, uint32_t bytes) {
    asm volatile("mbarrier.arrive.expect_tx.shared::cta.b64 _, [%0], %1;" ::"r"(bar), "r"(bytes) : "memory");
}
__device__ __forceinline__ void mbar_arrive(uint32_t bar) {
    asm volatile("mbarrier.arrive.shared::cta.b64 _, [%0];" ::"r"(bar) : "memory");
}
__device__ __forceinline__ void mbar_arrive_remote(uint32_t bar, uint32_t cta) {
    asm volatile(
        "{\n.reg .b32 ra;\nmapa.shared::cluster.u32 ra, %0, %1;\n"
        "mbarrier.arrive.shared::cluster.b64 _, [ra];\n}\n" ::"r"(bar),
        "r"(cta)
        : "memory");
}
__device__ __forceinline__ void mbar_wait(uint32_t bar, uint32_t parity) {
    uint32_t ok;
    int it = 0;
    do {
        asm volatile(
            "{\n.reg .pred p;\nmbarrier.try_wait.parity.shared::cta.b64 p, [%1], %2;\nselp.u32 %0, 1, 0, p;\n}\n"
            : "=r"(ok)
            : "r"(bar), "r"(parity)
            : "memory");
        if (++it > (1 << 22)) __trap();
    } while (!ok);
}
__device__ __forceinline__ void mbar_wait_cluster(uint32_t bar, uint32_t parity) {
    uint32_t ok;
    int it = 0;
    do {
        asm volatile(
            "{\n.reg .pred p;\nmbarrier.try_wait.parity.shared::cta.b64 p, [%1], %2;\nselp.u32 %0, 1, 0, p;\n}\n"
            : "=r"(ok)
            : "r"(bar), "r"(parity)
            : "memory");
        if (++it > (1 << 22)) __trap();
    } while (!ok);
}
__device__ __forceinline__ void tma_load_2d(uint32_t dst, const CUtensorMap* map, int c0, int c1, uint32_t bar) {
    asm volatile(
        "cp.async.bulk.tensor.2d.shared::cluster.global.mbarrier::complete_tx::bytes [%0], [%1, {%3, %4}], [%2];" ::"r"(dst),
        "l"(map), "r"(bar), "r"(c0), "r"(c1)
        : "memory");
}
__device__ __forceinline__ void tma_load_2d_mc(uint32_t dst, const CUtensorMap* map, int c0, int c1, uint32_t bar,
                                               uint16_t mask) {
    asm volatile(
        "cp.async.bulk.tensor.2d.shared::cluster.global.mbarrier::complete_tx::bytes.multicast::cluster [%0], [%1, {%3, %4}], [%2], %5;" ::"r"(dst),
        "l"(map), "r"(bar), "r"(c0), "r"(c1), "h"(mask)
        : "memory");
}
__device__ __forceinline__ void prefetch_tmap(const CUtensorMap* map) {
    asm volatile("prefetch.tensormap [%0];" ::"l"(map) : "memory");
}
__device__ __forceinline__ void fence_proxy_async() { asm volatile("fence.proxy.async.shared::cta;" ::: "memory"); }
__device__ __forceinline__ void fence_mbar_init() { asm volatile("fence.mbarrier_init.release.cluster;" ::: "memory"); }
__device__ __forceinline__ void cluster_sync() {
    asm volatile("barrier.cluster.arrive.release.aligned;\nbarrier.cluster.wait.acquire.aligned;" ::: "memory");
}
__device__ __forceinline__ uint32_t cluster_ctarank() {
    uint32_t r;
    asm volatile("mov.u32 %0, %%cluster_ctarank;" : "=r"(r));
    return r;
}
__device__ __forceinline__ void named_bar_sync(int id, int nthreads) {
    asm volatile("bar.sync %0, %1;" ::"r"(id), "r"(nthreads) : "memory");
}
__device__ __forceinline__ void wgmma_fence() { asm volatile("wgmma.fence.sync.aligned;" ::: "memory"); }
__device__ __forceinline__ void wgmma_commit() { asm volatile("wgmma.commit_group.sync.aligned;" ::: "memory"); }
template <int N>
__device__ __forceinline__ void wgmma_wait() {
    asm volatile("wgmma.wait_group.sync.aligned %0;" ::"n"(N) : "memory");
}
__device__ __forceinline__ uint64_t make_desc(uint32_t addr, uint32_t lbo_bytes, uint32_t sbo_bytes) {
    return (uint64_t)((addr & 0x3FFFF) >> 4) | ((uint64_t)(lbo_bytes >> 4) << 16) | ((uint64_t)(sbo_bytes >> 4) << 32) |
           (1ull << 62);
}

template <int TB>
__device__ __forceinline__ void wgmma_n64(float (&d)[32], uint64_t da, uint64_t db, int scale_d) {
    asm volatile(
        "{\n.reg .pred p;\nsetp.ne.b32 p, %34, 0;\n"
        "wgmma.mma_async.sync.aligned.m64n64k16.f32.bf16.bf16 "
        "{%0, %1, %2, %3, %4, %5, %6, %7, %8, %9, %10, %11, %12, %13, %14, %15, %16, %17, %18, %19, %20, %21, %22, %23, %24, %25, %26, %27, %28, %29, %30, %31}, "
        "%32, %33, p, 1, 1, 0, %35;\n}\n"
        : "+f"(d[0]), "+f"(d[1]), "+f"(d[2]), "+f"(d[3]), "+f"(d[4]), "+f"(d[5]), "+f"(d[6]), "+f"(d[7]), "+f"(d[8]), "+f"(d[9]), "+f"(d[10]), "+f"(d[11]), "+f"(d[12]), "+f"(d[13]), "+f"(d[14]), "+f"(d[15]), "+f"(d[16]), "+f"(d[17]), "+f"(d[18]), "+f"(d[19]), "+f"(d[20]), "+f"(d[21]), "+f"(d[22]), "+f"(d[23]), "+f"(d[24]), "+f"(d[25]), "+f"(d[26]), "+f"(d[27]), "+f"(d[28]), "+f"(d[29]), "+f"(d[30]), "+f"(d[31])
        : "l"(da), "l"(db), "r"(scale_d), "n"(TB));
}

template <int TB>
__device__ __forceinline__ void wgmma_n128(float (&d)[64], uint64_t da, uint64_t db, int scale_d) {
    asm volatile(
        "{\n.reg .pred p;\nsetp.ne.b32 p, %66, 0;\n"
        "wgmma.mma_async.sync.aligned.m64n128k16.f32.bf16.bf16 "
        "{%0, %1, %2, %3, %4, %5, %6, %7, %8, %9, %10, %11, %12, %13, %14, %15, %16, %17, %18, %19, %20, %21, %22, %23, %24, %25, %26, %27, %28, %29, %30, %31, %32, %33, %34, %35, %36, %37, %38, %39, %40, %41, %42, %43, %44, %45, %46, %47, %48, %49, %50, %51, %52, %53, %54, %55, %56, %57, %58, %59, %60, %61, %62, %63}, "
        "%64, %65, p, 1, 1, 0, %67;\n}\n"
        : "+f"(d[0]), "+f"(d[1]), "+f"(d[2]), "+f"(d[3]), "+f"(d[4]), "+f"(d[5]), "+f"(d[6]), "+f"(d[7]), "+f"(d[8]), "+f"(d[9]), "+f"(d[10]), "+f"(d[11]), "+f"(d[12]), "+f"(d[13]), "+f"(d[14]), "+f"(d[15]), "+f"(d[16]), "+f"(d[17]), "+f"(d[18]), "+f"(d[19]), "+f"(d[20]), "+f"(d[21]), "+f"(d[22]), "+f"(d[23]), "+f"(d[24]), "+f"(d[25]), "+f"(d[26]), "+f"(d[27]), "+f"(d[28]), "+f"(d[29]), "+f"(d[30]), "+f"(d[31]), "+f"(d[32]), "+f"(d[33]), "+f"(d[34]), "+f"(d[35]), "+f"(d[36]), "+f"(d[37]), "+f"(d[38]), "+f"(d[39]), "+f"(d[40]), "+f"(d[41]), "+f"(d[42]), "+f"(d[43]), "+f"(d[44]), "+f"(d[45]), "+f"(d[46]), "+f"(d[47]), "+f"(d[48]), "+f"(d[49]), "+f"(d[50]), "+f"(d[51]), "+f"(d[52]), "+f"(d[53]), "+f"(d[54]), "+f"(d[55]), "+f"(d[56]), "+f"(d[57]), "+f"(d[58]), "+f"(d[59]), "+f"(d[60]), "+f"(d[61]), "+f"(d[62]), "+f"(d[63])
        : "l"(da), "l"(db), "r"(scale_d), "n"(TB));
}

template <int TB>
__device__ __forceinline__ void wgmma_n176(float (&d)[88], uint64_t da, uint64_t db, int scale_d) {
    asm volatile(
        "{\n.reg .pred p;\nsetp.ne.b32 p, %90, 0;\n"
        "wgmma.mma_async.sync.aligned.m64n176k16.f32.bf16.bf16 "
        "{%0, %1, %2, %3, %4, %5, %6, %7, %8, %9, %10, %11, %12, %13, %14, %15, %16, %17, %18, %19, %20, %21, %22, %23, %24, %25, %26, %27, %28, %29, %30, %31, %32, %33, %34, %35, %36, %37, %38, %39, %40, %41, %42, %43, %44, %45, %46, %47, %48, %49, %50, %51, %52, %53, %54, %55, %56, %57, %58, %59, %60, %61, %62, %63, %64, %65, %66, %67, %68, %69, %70, %71, %72, %73, %74, %75, %76, %77, %78, %79, %80, %81, %82, %83, %84, %85, %86, %87}, "
        "%88, %89, p, 1, 1, 0, %91;\n}\n"
        : "+f"(d[0]), "+f"(d[1]), "+f"(d[2]), "+f"(d[3]), "+f"(d[4]), "+f"(d[5]), "+f"(d[6]), "+f"(d[7]), "+f"(d[8]), "+f"(d[9]), "+f"(d[10]), "+f"(d[11]), "+f"(d[12]), "+f"(d[13]), "+f"(d[14]), "+f"(d[15]), "+f"(d[16]), "+f"(d[17]), "+f"(d[18]), "+f"(d[19]), "+f"(d[20]), "+f"(d[21]), "+f"(d[22]), "+f"(d[23]), "+f"(d[24]), "+f"(d[25]), "+f"(d[26]), "+f"(d[27]), "+f"(d[28]), "+f"(d[29]), "+f"(d[30]), "+f"(d[31]), "+f"(d[32]), "+f"(d[33]), "+f"(d[34]), "+f"(d[35]), "+f"(d[36]), "+f"(d[37]), "+f"(d[38]), "+f"(d[39]), "+f"(d[40]), "+f"(d[41]), "+f"(d[42]), "+f"(d[43]), "+f"(d[44]), "+f"(d[45]), "+f"(d[46]), "+f"(d[47]), "+f"(d[48]), "+f"(d[49]), "+f"(d[50]), "+f"(d[51]), "+f"(d[52]), "+f"(d[53]), "+f"(d[54]), "+f"(d[55]), "+f"(d[56]), "+f"(d[57]), "+f"(d[58]), "+f"(d[59]), "+f"(d[60]), "+f"(d[61]), "+f"(d[62]), "+f"(d[63]), "+f"(d[64]), "+f"(d[65]), "+f"(d[66]), "+f"(d[67]), "+f"(d[68]), "+f"(d[69]), "+f"(d[70]), "+f"(d[71]), "+f"(d[72]), "+f"(d[73]), "+f"(d[74]), "+f"(d[75]), "+f"(d[76]), "+f"(d[77]), "+f"(d[78]), "+f"(d[79]), "+f"(d[80]), "+f"(d[81]), "+f"(d[82]), "+f"(d[83]), "+f"(d[84]), "+f"(d[85]), "+f"(d[86]), "+f"(d[87])
        : "l"(da), "l"(db), "r"(scale_d), "n"(TB));
}

template <int TB>
__device__ __forceinline__ void wgmma_n256(float (&d)[128], uint64_t da, uint64_t db, int scale_d) {
    asm volatile(
        "{\n.reg .pred p;\nsetp.ne.b32 p, %130, 0;\n"
        "wgmma.mma_async.sync.aligned.m64n256k16.f32.bf16.bf16 "
        "{%0, %1, %2, %3, %4, %5, %6, %7, %8, %9, %10, %11, %12, %13, %14, %15, %16, %17, %18, %19, %20, %21, %22, %23, %24, %25, %26, %27, %28, %29, %30, %31, %32, %33, %34, %35, %36, %37, %38, %39, %40, %41, %42, %43, %44, %45, %46, %47, %48, %49, %50, %51, %52, %53, %54, %55, %56, %57, %58, %59, %60, %61, %62, %63, %64, %65, %66, %67, %68, %69, %70, %71, %72, %73, %74, %75, %76, %77, %78, %79, %80, %81, %82, %83, %84, %85, %86, %87, %88, %89, %90, %91, %92, %93, %94, %95, %96, %97, %98, %99, %100, %101, %102, %103, %104, %105, %106, %107, %108, %109, %110, %111, %112, %113, %114, %115, %116, %117, %118, %119, %120, %121, %122, %123, %124, %125, %126, %127}, "
        "%128, %129, p, 1, 1, 0, %131;\n}\n"
        : "+f"(d[0]), "+f"(d[1]), "+f"(d[2]), "+f"(d[3]), "+f"(d[4]), "+f"(d[5]), "+f"(d[6]), "+f"(d[7]), "+f"(d[8]), "+f"(d[9]), "+f"(d[10]), "+f"(d[11]), "+f"(d[12]), "+f"(d[13]), "+f"(d[14]), "+f"(d[15]), "+f"(d[16]), "+f"(d[17]), "+f"(d[18]), "+f"(d[19]), "+f"(d[20]), "+f"(d[21]), "+f"(d[22]), "+f"(d[23]), "+f"(d[24]), "+f"(d[25]), "+f"(d[26]), "+f"(d[27]), "+f"(d[28]), "+f"(d[29]), "+f"(d[30]), "+f"(d[31]), "+f"(d[32]), "+f"(d[33]), "+f"(d[34]), "+f"(d[35]), "+f"(d[36]), "+f"(d[37]), "+f"(d[38]), "+f"(d[39]), "+f"(d[40]), "+f"(d[41]), "+f"(d[42]), "+f"(d[43]), "+f"(d[44]), "+f"(d[45]), "+f"(d[46]), "+f"(d[47]), "+f"(d[48]), "+f"(d[49]), "+f"(d[50]), "+f"(d[51]), "+f"(d[52]), "+f"(d[53]), "+f"(d[54]), "+f"(d[55]), "+f"(d[56]), "+f"(d[57]), "+f"(d[58]), "+f"(d[59]), "+f"(d[60]), "+f"(d[61]), "+f"(d[62]), "+f"(d[63]), "+f"(d[64]), "+f"(d[65]), "+f"(d[66]), "+f"(d[67]), "+f"(d[68]), "+f"(d[69]), "+f"(d[70]), "+f"(d[71]), "+f"(d[72]), "+f"(d[73]), "+f"(d[74]), "+f"(d[75]), "+f"(d[76]), "+f"(d[77]), "+f"(d[78]), "+f"(d[79]), "+f"(d[80]), "+f"(d[81]), "+f"(d[82]), "+f"(d[83]), "+f"(d[84]), "+f"(d[85]), "+f"(d[86]), "+f"(d[87]), "+f"(d[88]), "+f"(d[89]), "+f"(d[90]), "+f"(d[91]), "+f"(d[92]), "+f"(d[93]), "+f"(d[94]), "+f"(d[95]), "+f"(d[96]), "+f"(d[97]), "+f"(d[98]), "+f"(d[99]), "+f"(d[100]), "+f"(d[101]), "+f"(d[102]), "+f"(d[103]), "+f"(d[104]), "+f"(d[105]), "+f"(d[106]), "+f"(d[107]), "+f"(d[108]), "+f"(d[109]), "+f"(d[110]), "+f"(d[111]), "+f"(d[112]), "+f"(d[113]), "+f"(d[114]), "+f"(d[115]), "+f"(d[116]), "+f"(d[117]), "+f"(d[118]), "+f"(d[119]), "+f"(d[120]), "+f"(d[121]), "+f"(d[122]), "+f"(d[123]), "+f"(d[124]), "+f"(d[125]), "+f"(d[126]), "+f"(d[127])
        : "l"(da), "l"(db), "r"(scale_d), "n"(TB));
}


template <int BN, int TB>
__device__ __forceinline__ void wgmma_bn(float (&d)[BN / 2], uint64_t da, uint64_t db, int scale_d) {
    if constexpr (BN == 64) wgmma_n64<TB>(d, da, db, scale_d);
    else if constexpr (BN == 128) wgmma_n128<TB>(d, da, db, scale_d);
    else if constexpr (BN == 176) wgmma_n176<TB>(d, da, db, scale_d);
    else wgmma_n256<TB>(d, da, db, scale_d);
}

__device__ __forceinline__ void pdl_wait() { asm volatile("griddepcontrol.wait;" ::: "memory"); }
__device__ __forceinline__ void pdl_launch() { asm volatile("griddepcontrol.launch_dependents;" ::: "memory"); }

__device__ __forceinline__ uint32_t pack_bf16(float a, float b) {
    __nv_bfloat162 v = __floats2bfloat162_rn(a, b);
    return *reinterpret_cast<uint32_t*>(&v);
}

__device__ __forceinline__ void mod_part(const __nv_bfloat16* __restrict__ c, const __nv_bfloat16* __restrict__ w_mod) {
    __shared__ float sc[D_];
    __shared__ float red[64][33];
    for (int i = threadIdx.x; i < D_; i += 256) {
        float v = __bfloat162float(c[i]);
        float s = v / (1.0f + __expf(-v));
        sc[i] = __bfloat162float(__float2bfloat16(s));
    }
    __syncthreads();
    const int chunk = threadIdx.x & 3, rg = threadIdx.x >> 2;
    const int col0 = blockIdx.x * 32 + chunk * 8;
    uint4 v[8];
#pragma unroll
    for (int r = 0; r < 8; r++) v[r] = *reinterpret_cast<const uint4*>(w_mod + (size_t)(rg * 8 + r) * (6 * D_) + col0);
    float acc[8];
#pragma unroll
    for (int j = 0; j < 8; j++) acc[j] = 0.f;
#pragma unroll
    for (int r = 0; r < 8; r++) {
        float s = sc[rg * 8 + r];
        const __nv_bfloat162* p = reinterpret_cast<const __nv_bfloat162*>(&v[r]);
#pragma unroll
        for (int j = 0; j < 4; j++) {
            float2 f = __bfloat1622float2(p[j]);
            acc[2 * j] += s * f.x;
            acc[2 * j + 1] += s * f.y;
        }
    }
#pragma unroll
    for (int j = 0; j < 8; j++) red[rg][chunk * 8 + j] = acc[j];
    __syncthreads();
    if (threadIdx.x < 32) {
        float s = 0.f;
#pragma unroll 8
        for (int r = 0; r < 64; r++) s += red[r][threadIdx.x];
        g_mod[blockIdx.x * 32 + threadIdx.x] = __bfloat162float(__float2bfloat16(s));
        __threadfence();
        if (threadIdx.x == 0) atomicAdd(&g_mod_cnt, 1u);
    }
    __syncthreads();
}

template <int LNV>
__global__ void __launch_bounds__(256) combine_kernel(const __nv_bfloat16* __restrict__ x, const __nv_bfloat16* __restrict__ c,
                                                      const __nv_bfloat16* __restrict__ w_mod,
                                                      const __nv_bfloat16* __restrict__ ws_re,
                                                      const __nv_bfloat16* __restrict__ ws_im) {
    const int warp = threadIdx.x >> 5, lane = threadIdx.x & 31;
    if constexpr (LNV == 1) {
        if (threadIdx.x == 0) {
            asm volatile("cp.async.bulk.prefetch.L2.global [%0], %1;" ::"l"(ws_re + (size_t)blockIdx.x * 16384), "r"(32768) : "memory");
            asm volatile("cp.async.bulk.prefetch.L2.global [%0], %1;" ::"l"(ws_im + (size_t)blockIdx.x * 16384), "r"(32768) : "memory");
        }
    }
    const int row = blockIdx.x * 8 + warp;
    const size_t base = (size_t)row * D_;
    if constexpr (LNV == 1) {
        if (blockIdx.x < 96) mod_part(c, w_mod);
    } else {
        pdl_launch();
    }
    uint4 pv[4][2], xv[2];
    xv[0] = *reinterpret_cast<const uint4*>(x + base + lane * 8);
    xv[1] = *reinterpret_cast<const uint4*>(x + base + 256 + lane * 8);
    if constexpr (LNV == 1) {
        if (threadIdx.x == 0) {
            volatile unsigned int* cnt = &g_mod_cnt;
            int it = 0;
            while (*cnt < 96u) {
                __nanosleep(64);
                if (++it > (1 << 22)) __trap();
            }
            __threadfence();
        }
        __syncthreads();
    }
    float f[16];
    if constexpr (LNV == 1) {
#pragma unroll
        for (int h = 0; h < 2; h++) {
            const __nv_bfloat162* xp = reinterpret_cast<const __nv_bfloat162*>(&xv[h]);
#pragma unroll
            for (int j = 0; j < 4; j++) {
                float2 xx = __bfloat1622float2(xp[j]);
                f[h * 8 + 2 * j] = xx.x;
                f[h * 8 + 2 * j + 1] = xx.y;
            }
        }
    } else {
#pragma unroll
    for (int q = 0; q < 4; q++) {
        pv[q][0] = *reinterpret_cast<const uint4*>(g_part + (size_t)q * S_ * D_ + base + lane * 8);
        pv[q][1] = *reinterpret_cast<const uint4*>(g_part + (size_t)q * S_ * D_ + base + 256 + lane * 8);
    }
#pragma unroll
    for (int h = 0; h < 2; h++) {
        const __nv_bfloat162* p0 = reinterpret_cast<const __nv_bfloat162*>(&pv[0][h]);
        const __nv_bfloat162* p1 = reinterpret_cast<const __nv_bfloat162*>(&pv[1][h]);
        const __nv_bfloat162* p2 = reinterpret_cast<const __nv_bfloat162*>(&pv[2][h]);
        const __nv_bfloat162* p3 = reinterpret_cast<const __nv_bfloat162*>(&pv[3][h]);
        const __nv_bfloat162* xp = reinterpret_cast<const __nv_bfloat162*>(&xv[h]);
        const float* ga = g_mod + 2 * D_ + h * 256 + lane * 8;
#pragma unroll
        for (int j = 0; j < 4; j++) {
            float2 a0 = __bfloat1622float2(p0[j]), a1 = __bfloat1622float2(p1[j]);
            float2 a2 = __bfloat1622float2(p2[j]), a3 = __bfloat1622float2(p3[j]);
            float2 xx = __bfloat1622float2(xp[j]);
            f[h * 8 + 2 * j] = __bfloat162float(__float2bfloat16(xx.x + ga[2 * j] * ((a0.x + a1.x) - (a2.x + a3.x))));
            f[h * 8 + 2 * j + 1] = __bfloat162float(__float2bfloat16(xx.y + ga[2 * j + 1] * ((a0.y + a1.y) - (a2.y + a3.y))));
        }
    }
    {
        uint4 o0, o1;
        o0.x = pack_bf16(f[0], f[1]); o0.y = pack_bf16(f[2], f[3]); o0.z = pack_bf16(f[4], f[5]); o0.w = pack_bf16(f[6], f[7]);
        o1.x = pack_bf16(f[8], f[9]); o1.y = pack_bf16(f[10], f[11]); o1.z = pack_bf16(f[12], f[13]); o1.w = pack_bf16(f[14], f[15]);
        *reinterpret_cast<uint4*>(g_x1 + base + lane * 8) = o0;
        *reinterpret_cast<uint4*>(g_x1 + base + 256 + lane * 8) = o1;
    }
    }
    float s = 0.f;
#pragma unroll
    for (int j = 0; j < 16; j++) s += f[j];
#pragma unroll
    for (int o = 16; o > 0; o >>= 1) s += __shfl_xor_sync(0xffffffffu, s, o);
    const float mean = s * (1.0f / D_);
    float q = 0.f;
#pragma unroll
    for (int j = 0; j < 16; j++) {
        f[j] -= mean;
        q += f[j] * f[j];
    }
#pragma unroll
    for (int o = 16; o > 0; o >>= 1) q += __shfl_xor_sync(0xffffffffu, q, o);
    const float rstd = rsqrtf(q * (1.0f / D_) + 1e-5f);
    uint32_t o[8];
#pragma unroll
    for (int h = 0; h < 2; h++) {
        const float* sh = g_mod + (LNV == 1 ? 0 : 3) * D_ + h * 256 + lane * 8;
        const float* sc = g_mod + (LNV == 1 ? 1 : 4) * D_ + h * 256 + lane * 8;
#pragma unroll
        for (int j = 0; j < 4; j++)
            o[h * 4 + j] = pack_bf16(f[h * 8 + 2 * j] * rstd * (1.0f + sc[2 * j]) + sh[2 * j],
                                     f[h * 8 + 2 * j + 1] * rstd * (1.0f + sc[2 * j + 1]) + sh[2 * j + 1]);
    }
    *reinterpret_cast<uint4*>(g_h2 + base + lane * 8) = make_uint4(o[0], o[1], o[2], o[3]);
    *reinterpret_cast<uint4*>(g_h2 + base + 256 + lane * 8) = make_uint4(o[4], o[5], o[6], o[7]);
}

template <int VAR>
struct Cfg;
template <>
struct Cfg<1> {
    static constexpr int BN = 128, STAGES = 6, KT = 8, CL = 1;
    static constexpr bool A_RES = false, B_MN = false;
    static constexpr int B_STAGE = 16384;
};
template <>
struct Cfg<2> {
    static constexpr int BN = 256, STAGES = 4, KT = 16, CL = 2;
    static constexpr bool A_RES = false, B_MN = true;
    static constexpr int B_STAGE = 32768;
};
template <>
struct Cfg<3> {
    static constexpr int BN = 176, STAGES = 5, KT = 8, CL = 1;
    static constexpr bool A_RES = false, B_MN = true;
    static constexpr int B_STAGE = 24576;
};
template <>
struct Cfg<4> {
    static constexpr int BN = 64, STAGES = 8, KT = 22, CL = 2;
    static constexpr bool A_RES = false, B_MN = true;
    static constexpr int B_STAGE = 8192;
};

template <int VAR>
constexpr int smem_bytes() {
    using C = Cfg<VAR>;
    return (C::A_RES ? 131072 : C::STAGES * 16384) + C::STAGES * C::B_STAGE + 1024 + 256;
}

template <int VAR>
__global__ void __launch_bounds__(288, 1)
    gemm_kernel(const __grid_constant__ CUtensorMap tmA0, const __grid_constant__ CUtensorMap tmA1,
                const __grid_constant__ CUtensorMap tmB0, const __grid_constant__ CUtensorMap tmB1,
                const __nv_bfloat16* __restrict__ xin, __nv_bfloat16* __restrict__ out) {
    using C = Cfg<VAR>;
    constexpr int BN = C::BN, STAGES = C::STAGES, KT = C::KT, CL = C::CL;
    constexpr int A_BYTES = C::A_RES ? 131072 : STAGES * 16384;
    extern __shared__ uint8_t smem_raw[];
    const uint32_t smem_base = (smem_u32(smem_raw) + 1023u) & ~1023u;
    const uint32_t sA = smem_base;
    const uint32_t sB = smem_base + A_BYTES;
    const uint32_t bars = sB + STAGES * C::B_STAGE;
    const uint32_t full0 = bars, empty0 = bars + 8 * STAGES;

    const int tid = threadIdx.x, warp = tid >> 5, lane = tid & 31;

    int mt, nt, kq = 0;
    uint32_t rank = 0;
    if constexpr (VAR == 2) {
        rank = cluster_ctarank();
        const int cid = blockIdx.x >> 1;
        kq = cid & 3;
        nt = (cid >> 2) & 1;
        mt = (cid >> 3) * 2 + (int)rank;
    } else {
        if constexpr (CL > 1) rank = cluster_ctarank();
        mt = blockIdx.x / 8;
        nt = blockIdx.x % 8;
    }
    const int m0 = mt * 128;
    pdl_launch();

    if (tid == 0) {
        for (int i = 0; i < STAGES; i++) {
            mbar_init(full0 + 8 * i, 1);
            mbar_init(empty0 + 8 * i, 2 * CL);
        }
        fence_mbar_init();
    }
    if constexpr (CL > 1) cluster_sync();
    else __syncthreads();

    if (warp == 8) {
        if (lane == 0) {
            prefetch_tmap(&tmA0);
            prefetch_tmap(&tmB0);
            if constexpr (VAR == 2) {
                for (int i = 0; i < STAGES; i++) {
                    mbar_expect_tx(full0 + 8 * i, 16384 + C::B_STAGE);
                    tma_load_2d(sA + i * 16384, kq < 2 ? &tmA0 : &tmA1, (kq & 1) * 1024 + i * 64, m0, full0 + 8 * i);
                }
            }
            pdl_wait();
            int stage = 0, phase = 1;
            for (int kt = 0; kt < KT; kt++) {
                if constexpr (CL > 1) mbar_wait_cluster(empty0 + 8 * stage, phase);
                else mbar_wait(empty0 + 8 * stage, phase);
                const uint32_t fb = full0 + 8 * stage;
                if (VAR != 2 || kt >= STAGES) mbar_expect_tx(fb, (C::A_RES ? 0 : 16384) + C::B_STAGE);
                if constexpr (VAR == 1) {
                    tma_load_2d(sA + stage * 16384, &tmA0, kt * 64, m0, fb);
                    tma_load_2d(sB + stage * C::B_STAGE, nt < 4 ? &tmB0 : &tmB1, kt * 64, (nt & 3) * 128, fb);
                } else if constexpr (VAR == 2) {
                    const int k0 = (kq & 1) * 1024 + kt * 64;
                    if (kt >= STAGES) tma_load_2d(sA + stage * 16384, kq < 2 ? &tmA0 : &tmA1, k0, m0, fb);
#pragma unroll
                    for (int q = 0; q < 2; q++)
                        tma_load_2d_mc(sB + stage * C::B_STAGE + (rank * 2 + q) * 8192, &tmB0,
                                       (kq >> 1) * 512 + nt * 256 + (rank * 2 + q) * 64, k0, fb, (uint16_t)0x3);
                } else if constexpr (VAR == 3) {
                    tma_load_2d(sA + stage * 16384, &tmA0, kt * 64, m0, fb);
#pragma unroll
                    for (int q = 0; q < 3; q++)
                        tma_load_2d(sB + stage * C::B_STAGE + q * 8192, &tmB0, nt * 176 + q * 64, kt * 64, fb);
                } else {
                    tma_load_2d_mc(sA + stage * 16384 + rank * 8192, &tmA0, kt * 64, m0 + rank * 64, fb, (uint16_t)0x3);
                    tma_load_2d(sB + stage * C::B_STAGE, &tmB0, nt * 64, kt * 64, fb);
                }
                if (++stage == STAGES) {
                    stage = 0;
                    phase ^= 1;
                }
            }
        }
    } else {
        const int wg = warp >> 2;
        pdl_wait();
        if constexpr (VAR == 1) {
            if (blockIdx.x == 0 && tid == 0) g_mod_cnt = 0u;
        }
        if constexpr (C::A_RES) {
            const __nv_bfloat16* src = (VAR == 1) ? xin : g_x1;
            const float* msh = g_mod + (VAR == 1 ? 0 : 3 * D_);
            const float* msc = g_mod + (VAR == 1 ? 1 * D_ : 4 * D_);
            float sh[16], sc[16];
#pragma unroll
            for (int bt = 0; bt < 2; bt++) {
                uint4 v[8][2];
#pragma unroll
                for (int r = 0; r < 8; r++) {
                    const __nv_bfloat16* row = src + (size_t)(m0 + warp * 16 + bt * 8 + r) * D_;
                    v[r][0] = *reinterpret_cast<const uint4*>(row + lane * 8);
                    v[r][1] = *reinterpret_cast<const uint4*>(row + 256 + lane * 8);
                }
                if (bt == 0) {
#pragma unroll
                    for (int j = 0; j < 8; j++) {
                        sh[j] = msh[lane * 8 + j];
                        sc[j] = 1.0f + msc[lane * 8 + j];
                        sh[8 + j] = msh[256 + lane * 8 + j];
                        sc[8 + j] = 1.0f + msc[256 + lane * 8 + j];
                    }
                }
#pragma unroll
                for (int r = 0; r < 8; r++) {
                    float f[16];
                    const __nv_bfloat162* p0 = reinterpret_cast<const __nv_bfloat162*>(&v[r][0]);
                    const __nv_bfloat162* p1 = reinterpret_cast<const __nv_bfloat162*>(&v[r][1]);
#pragma unroll
                    for (int j = 0; j < 4; j++) {
                        float2 a = __bfloat1622float2(p0[j]);
                        f[2 * j] = a.x;
                        f[2 * j + 1] = a.y;
                        float2 b = __bfloat1622float2(p1[j]);
                        f[8 + 2 * j] = b.x;
                        f[8 + 2 * j + 1] = b.y;
                    }
                    float s = 0.f;
#pragma unroll
                    for (int j = 0; j < 16; j++) s += f[j];
#pragma unroll
                    for (int o = 16; o > 0; o >>= 1) s += __shfl_xor_sync(0xffffffffu, s, o);
                    const float mean = s * (1.0f / D_);
                    float q = 0.f;
#pragma unroll
                    for (int j = 0; j < 16; j++) {
                        f[j] -= mean;
                        q += f[j] * f[j];
                    }
#pragma unroll
                    for (int o = 16; o > 0; o >>= 1) q += __shfl_xor_sync(0xffffffffu, q, o);
                    const float rstd = rsqrtf(q * (1.0f / D_) + 1e-5f);
                    uint4 o0, o1;
                    uint32_t* o0p = reinterpret_cast<uint32_t*>(&o0);
                    uint32_t* o1p = reinterpret_cast<uint32_t*>(&o1);
#pragma unroll
                    for (int j = 0; j < 4; j++) {
                        o0p[j] = pack_bf16(f[2 * j] * rstd * sc[2 * j] + sh[2 * j], f[2 * j + 1] * rstd * sc[2 * j + 1] + sh[2 * j + 1]);
                        o1p[j] = pack_bf16(f[8 + 2 * j] * rstd * sc[8 + 2 * j] + sh[8 + 2 * j],
                                           f[8 + 2 * j + 1] * rstd * sc[8 + 2 * j + 1] + sh[8 + 2 * j + 1]);
                    }
                    const int row = warp * 16 + bt * 8 + r;
                    const uint32_t chunk = (uint32_t)(lane & 7) ^ (uint32_t)(row & 7);
                    const uint32_t a0 = sA + (lane >> 3) * 16384 + row * 128 + chunk * 16;
                    const uint32_t a1 = a0 + 4 * 16384;
                    asm volatile("st.shared.v4.b32 [%0], {%1, %2, %3, %4};" ::"r"(a0), "r"(o0.x), "r"(o0.y), "r"(o0.z), "r"(o0.w) : "memory");
                    asm volatile("st.shared.v4.b32 [%0], {%1, %2, %3, %4};" ::"r"(a1), "r"(o1.x), "r"(o1.y), "r"(o1.z), "r"(o1.w) : "memory");
                }
            }
            fence_proxy_async();
            named_bar_sync(1, 256);
        }

        float acc[BN / 2];
        int stage = 0, phase = 0;
        for (int kt = 0; kt < KT; kt++) {
            mbar_wait(full0 + 8 * stage, phase);
            const uint32_t a_base = (C::A_RES ? sA + kt * 16384 : sA + stage * 16384) + wg * 8192;
            const uint32_t b_base = sB + stage * C::B_STAGE;
            wgmma_fence();
#pragma unroll
            for (int k = 0; k < 4; k++) {
                const uint64_t da = make_desc(a_base + k * 32, 16, 1024);
                uint64_t db;
                if constexpr (C::B_MN) db = make_desc(b_base + k * 2048, 8192, 1024);
                else db = make_desc(b_base + k * 32, 16, 1024);
                wgmma_bn<BN, C::B_MN ? 1 : 0>(acc, da, db, (kt | k) != 0);
            }
            wgmma_commit();
            if (kt > 0) {
                wgmma_wait<1>();
                const int ps = (stage == 0) ? STAGES - 1 : stage - 1;
                if constexpr (CL > 1) {
                    if ((tid & 127) < CL) mbar_arrive_remote(empty0 + 8 * ps, tid & 127);
                } else {
                    if ((tid & 127) == 0) mbar_arrive(empty0 + 8 * ps);
                }
            }
            if (++stage == STAGES) {
                stage = 0;
                phase ^= 1;
            }
        }
        wgmma_wait<0>();

        const int r0 = wg * 64 + (warp & 3) * 16 + (lane >> 2);
        const int cq = (lane & 3) * 2;
        {
            named_bar_sync(2, 256);
            const uint32_t stg = smem_base + wg * 32768;
            const int rl = (warp & 3) * 16 + (lane >> 2);
            if constexpr (VAR == 4) {
                const __nv_bfloat16* xr = g_x1 + (size_t)(m0 + r0) * D_ + nt * 64 + cq;
                const float* gb = g_mod + 5 * D_ + nt * 64 + cq;
#pragma unroll
                for (int j = 0; j < BN / 8; j++) {
                    float2 xa = __bfloat1622float2(*reinterpret_cast<const __nv_bfloat162*>(xr + j * 8));
                    float2 xb = __bfloat1622float2(*reinterpret_cast<const __nv_bfloat162*>(xr + 8 * D_ + j * 8));
                    float g0 = gb[j * 8], g1 = gb[j * 8 + 1];
                    acc[4 * j + 0] = xa.x + g0 * acc[4 * j + 0];
                    acc[4 * j + 1] = xa.y + g1 * acc[4 * j + 1];
                    acc[4 * j + 2] = xb.x + g0 * acc[4 * j + 2];
                    acc[4 * j + 3] = xb.y + g1 * acc[4 * j + 3];
                }
            }
#pragma unroll
            for (int j = 0; j < BN / 8; j++) {
                float v0 = acc[4 * j], v1 = acc[4 * j + 1], v2 = acc[4 * j + 2], v3 = acc[4 * j + 3];
                if constexpr (VAR == 3) {
                    v0 = fmaxf(v0, 0.f);
                    v1 = fmaxf(v1, 0.f);
                    v2 = fmaxf(v2, 0.f);
                    v3 = fmaxf(v3, 0.f);
                }
                const uint32_t sub = stg + (j >> 3) * 8192;
                const uint32_t ch = (uint32_t)(j & 7);
                const uint32_t ad0 = sub + rl * 128 + ((ch ^ (uint32_t)(rl & 7)) << 4) + cq * 2;
                const uint32_t ad1 = sub + (rl + 8) * 128 + ((ch ^ (uint32_t)((rl + 8) & 7)) << 4) + cq * 2;
                asm volatile("st.shared.b32 [%0], %1;" ::"r"(ad0), "r"(pack_bf16(v0, v1)) : "memory");
                asm volatile("st.shared.b32 [%0], %1;" ::"r"(ad1), "r"(pack_bf16(v2, v3)) : "memory");
            }
            named_bar_sync(3 + wg, 128);
            constexpr int NCH = BN / 8;
            const int t = tid & 127;
            for (int i = t; i < 64 * NCH; i += 128) {
                const int row = i / NCH, ch = i % NCH;
                const uint32_t ad = stg + (ch >> 3) * 8192 + row * 128 + ((((uint32_t)ch & 7) ^ (uint32_t)(row & 7)) << 4);
                uint4 val;
                asm volatile("ld.shared.v4.b32 {%0, %1, %2, %3}, [%4];" : "=r"(val.x), "=r"(val.y), "=r"(val.z), "=r"(val.w) : "r"(ad));
                const int grow = m0 + wg * 64 + row;
                if constexpr (VAR == 1) {
                    *reinterpret_cast<uint4*>(g_ab + (size_t)grow * 1024 + nt * 128 + ch * 8) = val;
                } else if constexpr (VAR == 2) {
                    *reinterpret_cast<uint4*>(g_part + (size_t)kq * S_ * D_ + (size_t)grow * D_ + nt * 256 + ch * 8) = val;
                } else if constexpr (VAR == 3) {
                    const int gc = nt * 176 + ch * 8;
                    if (gc < DFF_) *reinterpret_cast<uint4*>(g_h1 + (size_t)grow * DFF_ + gc) = val;
                } else {
                    *reinterpret_cast<uint4*>(out + (size_t)grow * D_ + nt * 64 + ch * 8) = val;
                }
            }
        }
    }
    if constexpr (VAR == 2) {
        if (warp < 8) {
            __threadfence();
            named_bar_sync(5, 256);
            if (tid == 0) atomicAdd(&g_rb_cnt[mt], 1u);
            if (tid == 0) {
                volatile unsigned int* cnt = &g_rb_cnt[mt];
                int it = 0;
                while (*cnt < 8u) {
                    __nanosleep(32);
                    if (++it > (1 << 22)) __trap();
                }
                __threadfence();
            }
            named_bar_sync(6, 256);
            const int sub = kq * 2 + nt;
            uint4 xv[2][2], pq[2][4][2];
#pragma unroll
            for (int rr = 0; rr < 2; rr++) {
                const size_t base = (size_t)(m0 + sub * 16 + warp * 2 + rr) * D_;
#pragma unroll
                for (int h = 0; h < 2; h++) {
                    xv[rr][h] = *reinterpret_cast<const uint4*>(xin + base + h * 256 + lane * 8);
#pragma unroll
                    for (int q = 0; q < 4; q++)
                        pq[rr][q][h] = __ldcg(reinterpret_cast<const uint4*>(g_part + (size_t)q * S_ * D_ + base + h * 256 + lane * 8));
                }
            }
            float ga[16], sh[16], sc[16];
#pragma unroll
            for (int h = 0; h < 2; h++) {
#pragma unroll
                for (int v = 0; v < 2; v++) {
                    const float4 g4 = *reinterpret_cast<const float4*>(g_mod + 2 * D_ + h * 256 + lane * 8 + v * 4);
                    const float4 s4 = *reinterpret_cast<const float4*>(g_mod + 3 * D_ + h * 256 + lane * 8 + v * 4);
                    const float4 c4 = *reinterpret_cast<const float4*>(g_mod + 4 * D_ + h * 256 + lane * 8 + v * 4);
                    const int o = h * 8 + v * 4;
                    ga[o] = g4.x; ga[o + 1] = g4.y; ga[o + 2] = g4.z; ga[o + 3] = g4.w;
                    sh[o] = s4.x; sh[o + 1] = s4.y; sh[o + 2] = s4.z; sh[o + 3] = s4.w;
                    sc[o] = 1.0f + c4.x; sc[o + 1] = 1.0f + c4.y; sc[o + 2] = 1.0f + c4.z; sc[o + 3] = 1.0f + c4.w;
                }
            }
#pragma unroll
            for (int rr = 0; rr < 2; rr++) {
                const size_t base = (size_t)(m0 + sub * 16 + warp * 2 + rr) * D_;
                float f[16];
#pragma unroll
                for (int h = 0; h < 2; h++) {
#pragma unroll
                    for (int j = 0; j < 4; j++) {
                        float2 a0 = __bfloat1622float2(reinterpret_cast<const __nv_bfloat162*>(&pq[rr][0][h])[j]);
                        float2 a1 = __bfloat1622float2(reinterpret_cast<const __nv_bfloat162*>(&pq[rr][1][h])[j]);
                        float2 a2 = __bfloat1622float2(reinterpret_cast<const __nv_bfloat162*>(&pq[rr][2][h])[j]);
                        float2 a3 = __bfloat1622float2(reinterpret_cast<const __nv_bfloat162*>(&pq[rr][3][h])[j]);
                        float2 xx = __bfloat1622float2(reinterpret_cast<const __nv_bfloat162*>(&xv[rr][h])[j]);
                        const int o = h * 8 + 2 * j;
                        f[o] = __bfloat162float(__float2bfloat16(xx.x + ga[o] * ((a0.x + a1.x) - (a2.x + a3.x))));
                        f[o + 1] = __bfloat162float(__float2bfloat16(xx.y + ga[o + 1] * ((a0.y + a1.y) - (a2.y + a3.y))));
                    }
                }
                *reinterpret_cast<uint4*>(g_x1 + base + lane * 8) =
                    make_uint4(pack_bf16(f[0], f[1]), pack_bf16(f[2], f[3]), pack_bf16(f[4], f[5]), pack_bf16(f[6], f[7]));
                *reinterpret_cast<uint4*>(g_x1 + base + 256 + lane * 8) =
                    make_uint4(pack_bf16(f[8], f[9]), pack_bf16(f[10], f[11]), pack_bf16(f[12], f[13]), pack_bf16(f[14], f[15]));
                float sm = 0.f;
#pragma unroll
                for (int j = 0; j < 16; j++) sm += f[j];
#pragma unroll
                for (int o = 16; o > 0; o >>= 1) sm += __shfl_xor_sync(0xffffffffu, sm, o);
                const float mean = sm * (1.0f / D_);
                float qq = 0.f;
#pragma unroll
                for (int j = 0; j < 16; j++) { f[j] -= mean; qq += f[j] * f[j]; }
#pragma unroll
                for (int o = 16; o > 0; o >>= 1) qq += __shfl_xor_sync(0xffffffffu, qq, o);
                const float rstd = rsqrtf(qq * (1.0f / D_) + 1e-5f);
                uint32_t o[8];
#pragma unroll
                for (int j = 0; j < 8; j++)
                    o[j] = pack_bf16(f[2 * j] * rstd * sc[2 * j] + sh[2 * j], f[2 * j + 1] * rstd * sc[2 * j + 1] + sh[2 * j + 1]);
                *reinterpret_cast<uint4*>(g_h2 + base + lane * 8) = make_uint4(o[0], o[1], o[2], o[3]);
                *reinterpret_cast<uint4*>(g_h2 + base + 256 + lane * 8) = make_uint4(o[4], o[5], o[6], o[7]);
            }
        }
    }
    if constexpr (VAR == 3) {
        if (blockIdx.x < 16 && threadIdx.x == 0) g_rb_cnt[blockIdx.x] = 0u;
    }
    if constexpr (CL > 1) cluster_sync();
}

typedef CUresult (*EncodeFn)(CUtensorMap*, CUtensorMapDataType, cuuint32_t, void*, const cuuint64_t*, const cuuint64_t*,
                             const cuuint32_t*, const cuuint32_t*, CUtensorMapInterleave, CUtensorMapSwizzle,
                             CUtensorMapL2promotion, CUtensorMapFloatOOBfill);

void make_map(EncodeFn fn, CUtensorMap* m, const void* ptr, uint64_t inner, uint64_t outer, uint64_t pitch_bytes,
              uint32_t box_inner, uint32_t box_outer) {
    cuuint64_t dims[2] = {inner, outer};
    cuuint64_t strides[1] = {pitch_bytes};
    cuuint32_t box[2] = {box_inner, box_outer};
    cuuint32_t estr[2] = {1, 1};
    fn(m, CU_TENSOR_MAP_DATA_TYPE_BFLOAT16, 2, const_cast<void*>(ptr), dims, strides, box, estr,
       CU_TENSOR_MAP_INTERLEAVE_NONE, CU_TENSOR_MAP_SWIZZLE_128B, CU_TENSOR_MAP_L2_PROMOTION_L2_256B,
       CU_TENSOR_MAP_FLOAT_OOB_FILL_NONE);
}

template <int VAR>
void launch_gemm(int grid, const CUtensorMap& a0, const CUtensorMap& a1, const CUtensorMap& b0, const CUtensorMap& b1,
                 const __nv_bfloat16* xin, __nv_bfloat16* out, cudaStream_t st) {
    cudaLaunchConfig_t cfg = {};
    cfg.gridDim = dim3(grid);
    cfg.blockDim = dim3(288);
    cfg.dynamicSmemBytes = smem_bytes<VAR>();
    cfg.stream = st;
    cudaLaunchAttribute attr[2];
    attr[0].id = cudaLaunchAttributeClusterDimension;
    attr[0].val.clusterDim.x = Cfg<VAR>::CL;
    attr[0].val.clusterDim.y = 1;
    attr[0].val.clusterDim.z = 1;
    attr[1].id = cudaLaunchAttributeProgrammaticStreamSerialization;
    attr[1].val.programmaticStreamSerializationAllowed = 1;
    cfg.attrs = attr;
    cfg.numAttrs = 2;
    cudaLaunchKernelEx(&cfg, gemm_kernel<VAR>, a0, a1, b0, b1, xin, out);
}

template <int LNV>
void launch_ln(const __nv_bfloat16* x, const __nv_bfloat16* c, const __nv_bfloat16* w_mod, const __nv_bfloat16* ws_re,
               const __nv_bfloat16* ws_im, cudaStream_t st) {
    cudaLaunchConfig_t cfg = {};
    cfg.gridDim = dim3(S_ / 8);
    cfg.blockDim = dim3(256);
    cfg.stream = st;
    cudaLaunchAttribute attr[1];
    attr[0].id = cudaLaunchAttributeProgrammaticStreamSerialization;
    attr[0].val.programmaticStreamSerializationAllowed = 1;
    cfg.attrs = attr;
    cfg.numAttrs = PDL_LN;
    cudaLaunchKernelEx(&cfg, combine_kernel<LNV>, x, c, w_mod, ws_re, ws_im);
}

}

extern "C" void kernel_launch(void* const* d_in, const int* in_sizes, int n_in, void* d_out, int out_size) {
    const __nv_bfloat16* x = (const __nv_bfloat16*)d_in[0];
    const __nv_bfloat16* ws_re = (const __nv_bfloat16*)d_in[1];
    const __nv_bfloat16* ws_im = (const __nv_bfloat16*)d_in[2];
    const __nv_bfloat16* wd_re = (const __nv_bfloat16*)d_in[3];
    const __nv_bfloat16* wd_im = (const __nv_bfloat16*)d_in[4];
    const __nv_bfloat16* w1 = (const __nv_bfloat16*)d_in[6];
    const __nv_bfloat16* w2 = (const __nv_bfloat16*)d_in[7];
    const __nv_bfloat16* c = (const __nv_bfloat16*)d_in[8];
    const __nv_bfloat16* w_mod = (const __nv_bfloat16*)d_in[9];
    __nv_bfloat16* out = (__nv_bfloat16*)d_out;
    cudaStream_t st = cudaStreamPerThread;

    static EncodeFn enc = nullptr;
    static bool attr_done = false;
    if (!enc) {
        void* fn = nullptr;
        cudaDriverEntryPointQueryResult qres;
        cudaGetDriverEntryPoint("cuTensorMapEncodeTiled", &fn, cudaEnableDefault, &qres);
        enc = (EncodeFn)fn;
    }
    if (!attr_done) {
        cudaFuncSetAttribute(gemm_kernel<1>, cudaFuncAttributeMaxDynamicSharedMemorySize, smem_bytes<1>());
        cudaFuncSetAttribute(gemm_kernel<2>, cudaFuncAttributeMaxDynamicSharedMemorySize, smem_bytes<2>());
        cudaFuncSetAttribute(gemm_kernel<3>, cudaFuncAttributeMaxDynamicSharedMemorySize, smem_bytes<3>());
        cudaFuncSetAttribute(gemm_kernel<4>, cudaFuncAttributeMaxDynamicSharedMemorySize, smem_bytes<4>());
        attr_done = true;
    }
    void *p_ab, *p_h1, *p_h2;
    cudaGetSymbolAddress(&p_h2, g_h2);
    cudaGetSymbolAddress(&p_ab, g_ab);
    cudaGetSymbolAddress(&p_h1, g_h1);

    CUtensorMap tm_h2, tm_wdre, tm_wdim, tm_wsre, tm_wsim, tm_ab, tm_w1, tm_h1, tm_w2;
    make_map(enc, &tm_wdre, wd_re, D_, D_, D_ * 2, 64, 128);
    make_map(enc, &tm_wdim, wd_im, D_, D_, D_ * 2, 64, 128);
    make_map(enc, &tm_wsre, ws_re, S_, S_, S_ * 2, 64, 128);
    make_map(enc, &tm_wsim, ws_im, S_, S_, S_ * 2, 64, 128);
    make_map(enc, &tm_ab, p_ab, 1024, S_, 1024 * 2, 64, 64);
    make_map(enc, &tm_h2, p_h2, D_, S_, D_ * 2, 64, 128);
    make_map(enc, &tm_w1, w1, DFF_, D_, DFF_ * 2, 64, 64);
    make_map(enc, &tm_h1, p_h1, DFF_, S_, DFF_ * 2, 64, 64);
    make_map(enc, &tm_w2, w2, D_, DFF_, D_ * 2, 64, 64);

    launch_ln<1>(x, c, w_mod, ws_re, ws_im, st);
    launch_gemm<1>(128, tm_h2, tm_h2, tm_wdre, tm_wdim, x, nullptr, st);
    launch_gemm<2>(128, tm_wsre, tm_wsim, tm_ab, tm_ab, x, nullptr, st);
    launch_gemm<3>(128, tm_h2, tm_h2, tm_w1, tm_w1, nullptr, nullptr, st);
    launch_gemm<4>(128, tm_h1, tm_h1, tm_w2, tm_w2, nullptr, out, st);
}
```

```cpp
#include <cuda_runtime.h>
#include <cuda_bf16.h>
#include <cuda.h>
#include <stdint.h>

#define PDL_LN 0
namespace {

constexpr int S_ = 2048;
constexpr int D_ = 512;
constexpr int DFF_ = 1376;

__device__ float g_mod[6 * D_];
__device__ unsigned int g_mod_cnt;
__device__ unsigned int g_rb_cnt[16];
__device__ __align__(1024) __nv_bfloat16 g_ab[S_ * 1024];
__device__ __align__(1024) __nv_bfloat16 g_part[4 * S_ * D_];
__device__ __align__(1024) __nv_bfloat16 g_h2[S_ * D_];
__device__ __align__(1024) __nv_bfloat16 g_x1[S_ * D_];
__device__ __align__(1024) __nv_bfloat16 g_h1[S_ * DFF_];

__device__ __forceinline__ uint32_t smem_u32(const void* p) { return (uint32_t)__cvta_generic_to_shared(p); }

__device__ __forceinline__ void mbar_init(uint32_t bar, uint32_t count) {
    asm volatile("mbarrier.init.shared::cta.b64 [%0], %1;" ::"r"(bar), "r"(count) : "memory");
}
__device__ __forceinline__ void mbar_expect_tx(uint32_t bar, uint32_t bytes) {
    asm volatile("mbarrier.arrive.expect_tx.shared::cta.b64 _, [%0], %1;" ::"r"(bar), "r"(bytes) : "memory");
}
__device__ __forceinline__ void mbar_arrive(uint32_t bar) {
    asm volatile("mbarrier.arrive.shared::cta.b64 _, [%0];" ::"r"(bar) : "memory");
}
__device__ __forceinline__ void mbar_arrive_remote(uint32_t bar, uint32_t cta) {
    asm volatile(
        "{\n.reg .b32 ra;\nmapa.shared::cluster.u32 ra, %0, %1;\n"
        "mbarrier.arrive.shared::cluster.b64 _, [ra];\n}\n" ::"r"(bar),
        "r"(cta)
        : "memory");
}
__device__ __forceinline__ void mbar_wait(uint32_t bar, uint32_t parity) {
    uint32_t ok;
    int it = 0;
    do {
        asm volatile(
            "{\n.reg .pred p;\nmbarrier.try_wait.parity.shared::cta.b64 p, [%1], %2;\nselp.u32 %0, 1, 0, p;\n}\n"
            : "=r"(ok)
            : "r"(bar), "r"(parity)
            : "memory");
        if (++it > (1 << 22)) __trap();
    } while (!ok);
}
__device__ __forceinline__ void mbar_wait_cluster(uint32_t bar, uint32_t parity) {
    uint32_t ok;
    int it = 0;
    do {
        asm volatile(
            "{\n.reg .pred p;\nmbarrier.try_wait.parity.shared::cta.b64 p, [%1], %2;\nselp.u32 %0, 1, 0, p;\n}\n"
            : "=r"(ok)
            : "r"(bar), "r"(parity)
            : "memory");
        if (++it > (1 << 22)) __trap();
    } while (!ok);
}
__device__ __forceinline__ void tma_load_2d(uint32_t dst, const CUtensorMap* map, int c0, int c1, uint32_t bar) {
    asm volatile(
        "cp.async.bulk.tensor.2d.shared::cluster.global.mbarrier::complete_tx::bytes [%0], [%1, {%3, %4}], [%2];" ::"r"(dst),
        "l"(map), "r"(bar), "r"(c0), "r"(c1)
        : "memory");
}
__device__ __forceinline__ void tma_load_2d_mc(uint32_t dst, const CUtensorMap* map, int c0, int c1, uint32_t bar,
                                               uint16_t mask) {
    asm volatile(
        "cp.async.bulk.tensor.2d.shared::cluster.global.mbarrier::complete_tx::bytes.multicast::cluster [%0], [%1, {%3, %4}], [%2], %5;" ::"r"(dst),
        "l"(map), "r"(bar), "r"(c0), "r"(c1), "h"(mask)
        : "memory");
}
__device__ __forceinline__ void prefetch_tmap(const CUtensorMap* map) {
    asm volatile("prefetch.tensormap [%0];" ::"l"(map) : "memory");
}
__device__ __forceinline__ void fence_proxy_async() { asm volatile("fence.proxy.async.shared::cta;" ::: "memory"); }
__device__ __forceinline__ void fence_mbar_init() { asm volatile("fence.mbarrier_init.release.cluster;" ::: "memory"); }
__device__ __forceinline__ void cluster_sync() {
    asm volatile("barrier.cluster.arrive.release.aligned;\nbarrier.cluster.wait.acquire.aligned;" ::: "memory");
}
__device__ __forceinline__ uint32_t cluster_ctarank() {
    uint32_t r;
    asm volatile("mov.u32 %0, %%cluster_ctarank;" : "=r"(r));
    return r;
}
__device__ __forceinline__ void named_bar_sync(int id, int nthreads) {
    asm volatile("bar.sync %0, %1;" ::"r"(id), "r"(nthreads) : "memory");
}
__device__ __forceinline__ void wgmma_fence() { asm volatile("wgmma.fence.sync.aligned;" ::: "memory"); }
__device__ __forceinline__ void wgmma_commit() { asm volatile("wgmma.commit_group.sync.aligned;" ::: "memory"); }
template <int N>
__device__ __forceinline__ void wgmma_wait() {
    asm volatile("wgmma.wait_group.sync.aligned %0;" ::"n"(N) : "memory");
}
__device__ __forceinline__ uint64_t make_desc(uint32_t addr, uint32_t lbo_bytes, uint32_t sbo_bytes) {
    return (uint64_t)((addr & 0x3FFFF) >> 4) | ((uint64_t)(lbo_bytes >> 4) << 16) | ((uint64_t)(sbo_bytes >> 4) << 32) |
           (1ull << 62);
}

template <int TB>
__device__ __forceinline__ void wgmma_n64(float (&d)[32], uint64_t da, uint64_t db, int scale_d) {
    asm volatile(
        "{\n.reg .pred p;\nsetp.ne.b32 p, %34, 0;\n"
        "wgmma.mma_async.sync.aligned.m64n64k16.f32.bf16.bf16 "
        "{%0, %1, %2, %3, %4, %5, %6, %7, %8, %9, %10, %11, %12, %13, %14, %15, %16, %17, %18, %19, %20, %21, %22, %23, %24, %25, %26, %27, %28, %29, %30, %31}, "
        "%32, %33, p, 1, 1, 0, %35;\n}\n"
        : "+f"(d[0]), "+f"(d[1]), "+f"(d[2]), "+f"(d[3]), "+f"(d[4]), "+f"(d[5]), "+f"(d[6]), "+f"(d[7]), "+f"(d[8]), "+f"(d[9]), "+f"(d[10]), "+f"(d[11]), "+f"(d[12]), "+f"(d[13]), "+f"(d[14]), "+f"(d[15]), "+f"(d[16]), "+f"(d[17]), "+f"(d[18]), "+f"(d[19]), "+f"(d[20]), "+f"(d[21]), "+f"(d[22]), "+f"(d[23]), "+f"(d[24]), "+f"(d[25]), "+f"(d[26]), "+f"(d[27]), "+f"(d[28]), "+f"(d[29]), "+f"(d[30]), "+f"(d[31])
        : "l"(da), "l"(db), "r"(scale_d), "n"(TB));
}

template <int TB>
__device__ __forceinline__ void wgmma_n128(float (&d)[64], uint64_t da, uint64_t db, int scale_d) {
    asm volatile(
        "{\n.reg .pred p;\nsetp.ne.b32 p, %66, 0;\n"
        "wgmma.mma_async.sync.aligned.m64n128k16.f32.bf16.bf16 "
        "{%0, %1, %2, %3, %4, %5, %6, %7, %8, %9, %10, %11, %12, %13, %14, %15, %16, %17, %18, %19, %20, %21, %22, %23, %24, %25, %26, %27, %28, %29, %30, %31, %32, %33, %34, %35, %36, %37, %38, %39, %40, %41, %42, %43, %44, %45, %46, %47, %48, %49, %50, %51, %52, %53, %54, %55, %56, %57, %58, %59, %60, %61, %62, %63}, "
        "%64, %65, p, 1, 1, 0, %67;\n}\n"
        : "+f"(d[0]), "+f"(d[1]), "+f"(d[2]), "+f"(d[3]), "+f"(d[4]), "+f"(d[5]), "+f"(d[6]), "+f"(d[7]), "+f"(d[8]), "+f"(d[9]), "+f"(d[10]), "+f"(d[11]), "+f"(d[12]), "+f"(d[13]), "+f"(d[14]), "+f"(d[15]), "+f"(d[16]), "+f"(d[17]), "+f"(d[18]), "+f"(d[19]), "+f"(d[20]), "+f"(d[21]), "+f"(d[22]), "+f"(d[23]), "+f"(d[24]), "+f"(d[25]), "+f"(d[26]), "+f"(d[27]), "+f"(d[28]), "+f"(d[29]), "+f"(d[30]), "+f"(d[31]), "+f"(d[32]), "+f"(d[33]), "+f"(d[34]), "+f"(d[35]), "+f"(d[36]), "+f"(d[37]), "+f"(d[38]), "+f"(d[39]), "+f"(d[40]), "+f"(d[41]), "+f"(d[42]), "+f"(d[43]), "+f"(d[44]), "+f"(d[45]), "+f"(d[46]), "+f"(d[47]), "+f"(d[48]), "+f"(d[49]), "+f"(d[50]), "+f"(d[51]), "+f"(d[52]), "+f"(d[53]), "+f"(d[54]), "+f"(d[55]), "+f"(d[56]), "+f"(d[57]), "+f"(d[58]), "+f"(d[59]), "+f"(d[60]), "+f"(d[61]), "+f"(d[62]), "+f"(d[63])
        : "l"(da), "l"(db), "r"(scale_d), "n"(TB));
}

template <int TB>
__device__ __forceinline__ void wgmma_n176(float (&d)[88], uint64_t da, uint64_t db, int scale_d) {
    asm volatile(
        "{\n.reg .pred p;\nsetp.ne.b32 p, %90, 0;\n"
        "wgmma.mma_async.sync.aligned.m64n176k16.f32.bf16.bf16 "
        "{%0, %1, %2, %3, %4, %5, %6, %7, %8, %9, %10, %11, %12, %13, %14, %15, %16, %17, %18, %19, %20, %21, %22, %23, %24, %25, %26, %27, %28, %29, %30, %31, %32, %33, %34, %35, %36, %37, %38, %39, %40, %41, %42, %43, %44, %45, %46, %47, %48, %49, %50, %51, %52, %53, %54, %55, %56, %57, %58, %59, %60, %61, %62, %63, %64, %65, %66, %67, %68, %69, %70, %71, %72, %73, %74, %75, %76, %77, %78, %79, %80, %81, %82, %83, %84, %85, %86, %87}, "
        "%88, %89, p, 1, 1, 0, %91;\n}\n"
        : "+f"(d[0]), "+f"(d[1]), "+f"(d[2]), "+f"(d[3]), "+f"(d[4]), "+f"(d[5]), "+f"(d[6]), "+f"(d[7]), "+f"(d[8]), "+f"(d[9]), "+f"(d[10]), "+f"(d[11]), "+f"(d[12]), "+f"(d[13]), "+f"(d[14]), "+f"(d[15]), "+f"(d[16]), "+f"(d[17]), "+f"(d[18]), "+f"(d[19]), "+f"(d[20]), "+f"(d[21]), "+f"(d[22]), "+f"(d[23]), "+f"(d[24]), "+f"(d[25]), "+f"(d[26]), "+f"(d[27]), "+f"(d[28]), "+f"(d[29]), "+f"(d[30]), "+f"(d[31]), "+f"(d[32]), "+f"(d[33]), "+f"(d[34]), "+f"(d[35]), "+f"(d[36]), "+f"(d[37]), "+f"(d[38]), "+f"(d[39]), "+f"(d[40]), "+f"(d[41]), "+f"(d[42]), "+f"(d[43]), "+f"(d[44]), "+f"(d[45]), "+f"(d[46]), "+f"(d[47]), "+f"(d[48]), "+f"(d[49]), "+f"(d[50]), "+f"(d[51]), "+f"(d[52]), "+f"(d[53]), "+f"(d[54]), "+f"(d[55]), "+f"(d[56]), "+f"(d[57]), "+f"(d[58]), "+f"(d[59]), "+f"(d[60]), "+f"(d[61]), "+f"(d[62]), "+f"(d[63]), "+f"(d[64]), "+f"(d[65]), "+f"(d[66]), "+f"(d[67]), "+f"(d[68]), "+f"(d[69]), "+f"(d[70]), "+f"(d[71]), "+f"(d[72]), "+f"(d[73]), "+f"(d[74]), "+f"(d[75]), "+f"(d[76]), "+f"(d[77]), "+f"(d[78]), "+f"(d[79]), "+f"(d[80]), "+f"(d[81]), "+f"(d[82]), "+f"(d[83]), "+f"(d[84]), "+f"(d[85]), "+f"(d[86]), "+f"(d[87])
        : "l"(da), "l"(db), "r"(scale_d), "n"(TB));
}

template <int TB>
__device__ __forceinline__ void wgmma_n256(float (&d)[128], uint64_t da, uint64_t db, int scale_d) {
    asm volatile(
        "{\n.reg .pred p;\nsetp.ne.b32 p, %130, 0;\n"
        "wgmma.mma_async.sync.aligned.m64n256k16.f32.bf16.bf16 "
        "{%0, %1, %2, %3, %4, %5, %6, %7, %8, %9, %10, %11, %12, %13, %14, %15, %16, %17, %18, %19, %20, %21, %22, %23, %24, %25, %26, %27, %28, %29, %30, %31, %32, %33, %34, %35, %36, %37, %38, %39, %40, %41, %42, %43, %44, %45, %46, %47, %48, %49, %50, %51, %52, %53, %54, %55, %56, %57, %58, %59, %60, %61, %62, %63, %64, %65, %66, %67, %68, %69, %70, %71, %72, %73, %74, %75, %76, %77, %78, %79, %80, %81, %82, %83, %84, %85, %86, %87, %88, %89, %90, %91, %92, %93, %94, %95, %96, %97, %98, %99, %100, %101, %102, %103, %104, %105, %106, %107, %108, %109, %110, %111, %112, %113, %114, %115, %116, %117, %118, %119, %120, %121, %122, %123, %124, %125, %126, %127}, "
        "%128, %129, p, 1, 1, 0, %131;\n}\n"
        : "+f"(d[0]), "+f"(d[1]), "+f"(d[2]), "+f"(d[3]), "+f"(d[4]), "+f"(d[5]), "+f"(d[6]), "+f"(d[7]), "+f"(d[8]), "+f"(d[9]), "+f"(d[10]), "+f"(d[11]), "+f"(d[12]), "+f"(d[13]), "+f"(d[14]), "+f"(d[15]), "+f"(d[16]), "+f"(d[17]), "+f"(d[18]), "+f"(d[19]), "+f"(d[20]), "+f"(d[21]), "+f"(d[22]), "+f"(d[23]), "+f"(d[24]), "+f"(d[25]), "+f"(d[26]), "+f"(d[27]), "+f"(d[28]), "+f"(d[29]), "+f"(d[30]), "+f"(d[31]), "+f"(d[32]), "+f"(d[33]), "+f"(d[34]), "+f"(d[35]), "+f"(d[36]), "+f"(d[37]), "+f"(d[38]), "+f"(d[39]), "+f"(d[40]), "+f"(d[41]), "+f"(d[42]), "+f"(d[43]), "+f"(d[44]), "+f"(d[45]), "+f"(d[46]), "+f"(d[47]), "+f"(d[48]), "+f"(d[49]), "+f"(d[50]), "+f"(d[51]), "+f"(d[52]), "+f"(d[53]), "+f"(d[54]), "+f"(d[55]), "+f"(d[56]), "+f"(d[57]), "+f"(d[58]), "+f"(d[59]), "+f"(d[60]), "+f"(d[61]), "+f"(d[62]), "+f"(d[63]), "+f"(d[64]), "+f"(d[65]), "+f"(d[66]), "+f"(d[67]), "+f"(d[68]), "+f"(d[69]), "+f"(d[70]), "+f"(d[71]), "+f"(d[72]), "+f"(d[73]), "+f"(d[74]), "+f"(d[75]), "+f"(d[76]), "+f"(d[77]), "+f"(d[78]), "+f"(d[79]), "+f"(d[80]), "+f"(d[81]), "+f"(d[82]), "+f"(d[83]), "+f"(d[84]), "+f"(d[85]), "+f"(d[86]), "+f"(d[87]), "+f"(d[88]), "+f"(d[89]), "+f"(d[90]), "+f"(d[91]), "+f"(d[92]), "+f"(d[93]), "+f"(d[94]), "+f"(d[95]), "+f"(d[96]), "+f"(d[97]), "+f"(d[98]), "+f"(d[99]), "+f"(d[100]), "+f"(d[101]), "+f"(d[102]), "+f"(d[103]), "+f"(d[104]), "+f"(d[105]), "+f"(d[106]), "+f"(d[107]), "+f"(d[108]), "+f"(d[109]), "+f"(d[110]), "+f"(d[111]), "+f"(d[112]), "+f"(d[113]), "+f"(d[114]), "+f"(d[115]), "+f"(d[116]), "+f"(d[117]), "+f"(d[118]), "+f"(d[119]), "+f"(d[120]), "+f"(d[121]), "+f"(d[122]), "+f"(d[123]), "+f"(d[124]), "+f"(d[125]), "+f"(d[126]), "+f"(d[127])
        : "l"(da), "l"(db), "r"(scale_d), "n"(TB));
}


template <int BN, int TB>
__device__ __forceinline__ void wgmma_bn(float (&d)[BN / 2], uint64_t da, uint64_t db, int scale_d) {
    if constexpr (BN == 64) wgmma_n64<TB>(d, da, db, scale_d);
    else if constexpr (BN == 128) wgmma_n128<TB>(d, da, db, scale_d);
    else if constexpr (BN == 176) wgmma_n176<TB>(d, da, db, scale_d);
    else wgmma_n256<TB>(d, da, db, scale_d);
}

__device__ __forceinline__ void pdl_wait() { asm volatile("griddepcontrol.wait;" ::: "memory"); }
__device__ __forceinline__ void pdl_launch() { asm volatile("griddepcontrol.launch_dependents;" ::: "memory"); }

__device__ __forceinline__ uint32_t pack_bf16(float a, float b) {
    __nv_bfloat162 v = __floats2bfloat162_rn(a, b);
    return *reinterpret_cast<uint32_t*>(&v);
}

__device__ __forceinline__ void mod_part(const __nv_bfloat16* __restrict__ c, const __nv_bfloat16* __restrict__ w_mod) {
    __shared__ float sc[D_];
    __shared__ float red[64][33];
    for (int i = threadIdx.x; i < D_; i += 256) {
        float v = __bfloat162float(c[i]);
        float s = v / (1.0f + __expf(-v));
        sc[i] = __bfloat162float(__float2bfloat16(s));
    }
    __syncthreads();
    const int chunk = threadIdx.x & 3, rg = threadIdx.x >> 2;
    const int col0 = blockIdx.x * 32 + chunk * 8;
    uint4 v[8];
#pragma unroll
    for (int r = 0; r < 8; r++) v[r] = *reinterpret_cast<const uint4*>(w_mod + (size_t)(rg * 8 + r) * (6 * D_) + col0);
    float acc[8];
#pragma unroll
    for (int j = 0; j < 8; j++) acc[j] = 0.f;
#pragma unroll
    for (int r = 0; r < 8; r++) {
        float s = sc[rg * 8 + r];
        const __nv_bfloat162* p = reinterpret_cast<const __nv_bfloat162*>(&v[r]);
#pragma unroll
        for (int j = 0; j < 4; j++) {
            float2 f = __bfloat1622float2(p[j]);
            acc[2 * j] += s * f.x;
            acc[2 * j + 1] += s * f.y;
        }
    }
#pragma unroll
    for (int j = 0; j < 8; j++) red[rg][chunk * 8 + j] = acc[j];
    __syncthreads();
    if (threadIdx.x < 32) {
        float s = 0.f;
#pragma unroll 8
        for (int r = 0; r < 64; r++) s += red[r][threadIdx.x];
        g_mod[blockIdx.x * 32 + threadIdx.x] = __bfloat162float(__float2bfloat16(s));
        __threadfence();
        if (threadIdx.x == 0) atomicAdd(&g_mod_cnt, 1u);
    }
    __syncthreads();
}

template <int LNV>
__global__ void __launch_bounds__(256) combine_kernel(const __nv_bfloat16* __restrict__ x, const __nv_bfloat16* __restrict__ c,
                                                      const __nv_bfloat16* __restrict__ w_mod) {
    const int warp = threadIdx.x >> 5, lane = threadIdx.x & 31;
    const int row = blockIdx.x * 8 + warp;
    const size_t base = (size_t)row * D_;
    if constexpr (LNV == 1) {
        if (blockIdx.x < 96) mod_part(c, w_mod);
    } else {
        pdl_launch();
    }
    uint4 pv[4][2], xv[2];
    xv[0] = *reinterpret_cast<const uint4*>(x + base + lane * 8);
    xv[1] = *reinterpret_cast<const uint4*>(x + base + 256 + lane * 8);
    if constexpr (LNV == 1) {
        if (threadIdx.x == 0) {
            volatile unsigned int* cnt = &g_mod_cnt;
            int it = 0;
            while (*cnt < 96u) {
                __nanosleep(64);
                if (++it > (1 << 22)) __trap();
            }
            __threadfence();
        }
        __syncthreads();
    }
    float f[16];
    if constexpr (LNV == 1) {
#pragma unroll
        for (int h = 0; h < 2; h++) {
            const __nv_bfloat162* xp = reinterpret_cast<const __nv_bfloat162*>(&xv[h]);
#pragma unroll
            for (int j = 0; j < 4; j++) {
                float2 xx = __bfloat1622float2(xp[j]);
                f[h * 8 + 2 * j] = xx.x;
                f[h * 8 + 2 * j + 1] = xx.y;
            }
        }
    } else {
#pragma unroll
    for (int q = 0; q < 4; q++) {
        pv[q][0] = *reinterpret_cast<const uint4*>(g_part + (size_t)q * S_ * D_ + base + lane * 8);
        pv[q][1] = *reinterpret_cast<const uint4*>(g_part + (size_t)q * S_ * D_ + base + 256 + lane * 8);
    }
#pragma unroll
    for (int h = 0; h < 2; h++) {
        const __nv_bfloat162* p0 = reinterpret_cast<const __nv_bfloat162*>(&pv[0][h]);
        const __nv_bfloat162* p1 = reinterpret_cast<const __nv_bfloat162*>(&pv[1][h]);
        const __nv_bfloat162* p2 = reinterpret_cast<const __nv_bfloat162*>(&pv[2][h]);
        const __nv_bfloat162* p3 = reinterpret_cast<const __nv_bfloat162*>(&pv[3][h]);
        const __nv_bfloat162* xp = reinterpret_cast<const __nv_bfloat162*>(&xv[h]);
        const float* ga = g_mod + 2 * D_ + h * 256 + lane * 8;
#pragma unroll
        for (int j = 0; j < 4; j++) {
            float2 a0 = __bfloat1622float2(p0[j]), a1 = __bfloat1622float2(p1[j]);
            float2 a2 = __bfloat1622float2(p2[j]), a3 = __bfloat1622float2(p3[j]);
            float2 xx = __bfloat1622float2(xp[j]);
            f[h * 8 + 2 * j] = __bfloat162float(__float2bfloat16(xx.x + ga[2 * j] * ((a0.x + a1.x) - (a2.x + a3.x))));
            f[h * 8 + 2 * j + 1] = __bfloat162float(__float2bfloat16(xx.y + ga[2 * j + 1] * ((a0.y + a1.y) - (a2.y + a3.y))));
        }
    }
    {
        uint4 o0, o1;
        o0.x = pack_bf16(f[0], f[1]); o0.y = pack_bf16(f[2], f[3]); o0.z = pack_bf16(f[4], f[5]); o0.w = pack_bf16(f[6], f[7]);
        o1.x = pack_bf16(f[8], f[9]); o1.y = pack_bf16(f[10], f[11]); o1.z = pack_bf16(f[12], f[13]); o1.w = pack_bf16(f[14], f[15]);
        *reinterpret_cast<uint4*>(g_x1 + base + lane * 8) = o0;
        *reinterpret_cast<uint4*>(g_x1 + base + 256 + lane * 8) = o1;
    }
    }
    float s = 0.f;
#pragma unroll
    for (int j = 0; j < 16; j++) s += f[j];
#pragma unroll
    for (int o = 16; o > 0; o >>= 1) s += __shfl_xor_sync(0xffffffffu, s, o);
    const float mean = s * (1.0f / D_);
    float q = 0.f;
#pragma unroll
    for (int j = 0; j < 16; j++) {
        f[j] -= mean;
        q += f[j] * f[j];
    }
#pragma unroll
    for (int o = 16; o > 0; o >>= 1) q += __shfl_xor_sync(0xffffffffu, q, o);
    const float rstd = rsqrtf(q * (1.0f / D_) + 1e-5f);
    uint32_t o[8];
#pragma unroll
    for (int h = 0; h < 2; h++) {
        const float* sh = g_mod + (LNV == 1 ? 0 : 3) * D_ + h * 256 + lane * 8;
        const float* sc = g_mod + (LNV == 1 ? 1 : 4) * D_ + h * 256 + lane * 8;
#pragma unroll
        for (int j = 0; j < 4; j++)
            o[h * 4 + j] = pack_bf16(f[h * 8 + 2 * j] * rstd * (1.0f + sc[2 * j]) + sh[2 * j],
                                     f[h * 8 + 2 * j + 1] * rstd * (1.0f + sc[2 * j + 1]) + sh[2 * j + 1]);
    }
    *reinterpret_cast<uint4*>(g_h2 + base + lane * 8) = make_uint4(o[0], o[1], o[2], o[3]);
    *reinterpret_cast<uint4*>(g_h2 + base + 256 + lane * 8) = make_uint4(o[4], o[5], o[6], o[7]);
}

template <int VAR>
struct Cfg;
template <>
struct Cfg<1> {
    static constexpr int BN = 128, STAGES = 6, KT = 8, CL = 1;
    static constexpr bool A_RES = false, B_MN = false;
    static constexpr int B_STAGE = 16384;
};
template <>
struct Cfg<2> {
    static constexpr int BN = 256, STAGES = 4, KT = 16, CL = 2;
    static constexpr bool A_RES = false, B_MN = true;
    static constexpr int B_STAGE = 32768;
};
template <>
struct Cfg<3> {
    static constexpr int BN = 176, STAGES = 5, KT = 8, CL = 1;
    static constexpr bool A_RES = false, B_MN = true;
    static constexpr int B_STAGE = 24576;
};
template <>
struct Cfg<4> {
    static constexpr int BN = 64, STAGES = 8, KT = 22, CL = 2;
    static constexpr bool A_RES = false, B_MN = true;
    static constexpr int B_STAGE = 8192;
};

template <int VAR>
constexpr int smem_bytes() {
    using C = Cfg<VAR>;
    return (C::A_RES ? 131072 : C::STAGES * 16384) + C::STAGES * C::B_STAGE + 1024 + 256;
}

template <int VAR>
__global__ void __launch_bounds__(288, 1)
    gemm_kernel(const __grid_constant__ CUtensorMap tmA0, const __grid_constant__ CUtensorMap tmA1,
                const __grid_constant__ CUtensorMap tmB0, const __grid_constant__ CUtensorMap tmB1,
                const __nv_bfloat16* __restrict__ xin, __nv_bfloat16* __restrict__ out) {
    using C = Cfg<VAR>;
    constexpr int BN = C::BN, STAGES = C::STAGES, KT = C::KT, CL = C::CL;
    constexpr int A_BYTES = C::A_RES ? 131072 : STAGES * 16384;
    extern __shared__ uint8_t smem_raw[];
    const uint32_t smem_base = (smem_u32(smem_raw) + 1023u) & ~1023u;
    const uint32_t sA = smem_base;
    const uint32_t sB = smem_base + A_BYTES;
    const uint32_t bars = sB + STAGES * C::B_STAGE;
    const uint32_t full0 = bars, empty0 = bars + 8 * STAGES;

    const int tid = threadIdx.x, warp = tid >> 5, lane = tid & 31;

    int mt, nt, kq = 0;
    uint32_t rank = 0;
    if constexpr (VAR == 2) {
        rank = cluster_ctarank();
        const int cid = blockIdx.x >> 1;
        kq = cid & 3;
        nt = (cid >> 2) & 1;
        mt = (cid >> 3) * 2 + (int)rank;
    } else {
        if constexpr (CL > 1) rank = cluster_ctarank();
        mt = blockIdx.x / 8;
        nt = blockIdx.x % 8;
    }
    const int m0 = mt * 128;
    pdl_launch();

    if (tid == 0) {
        for (int i = 0; i < STAGES; i++) {
            mbar_init(full0 + 8 * i, 1);
            mbar_init(empty0 + 8 * i, 2 * CL);
        }
        fence_mbar_init();
    }
    if constexpr (CL > 1) cluster_sync();
    else __syncthreads();

    if (warp == 8) {
        if (lane == 0) {
            prefetch_tmap(&tmA0);
            prefetch_tmap(&tmB0);
            if constexpr (VAR == 2) {
                for (int i = 0; i < STAGES; i++) {
                    mbar_expect_tx(full0 + 8 * i, 16384 + C::B_STAGE);
                    tma_load_2d(sA + i * 16384, kq < 2 ? &tmA0 : &tmA1, (kq & 1) * 1024 + i * 64, m0, full0 + 8 * i);
                }
            }
            pdl_wait();
            int stage = 0, phase = 1;
            for (int kt = 0; kt < KT; kt++) {
                if constexpr (CL > 1) mbar_wait_cluster(empty0 + 8 * stage, phase);
                else mbar_wait(empty0 + 8 * stage, phase);
                const uint32_t fb = full0 + 8 * stage;
                if (VAR != 2 || kt >= STAGES) mbar_expect_tx(fb, (C::A_RES ? 0 : 16384) + C::B_STAGE);
                if constexpr (VAR == 1) {
                    tma_load_2d(sA + stage * 16384, &tmA0, kt * 64, m0, fb);
                    tma_load_2d(sB + stage * C::B_STAGE, nt < 4 ? &tmB0 : &tmB1, kt * 64, (nt & 3) * 128, fb);
                } else if constexpr (VAR == 2) {
                    const int k0 = (kq & 1) * 1024 + kt * 64;
                    if (kt >= STAGES) tma_load_2d(sA + stage * 16384, kq < 2 ? &tmA0 : &tmA1, k0, m0, fb);
#pragma unroll
                    for (int q = 0; q < 2; q++)
                        tma_load_2d_mc(sB + stage * C::B_STAGE + (rank * 2 + q) * 8192, &tmB0,
                                       (kq >> 1) * 512 + nt * 256 + (rank * 2 + q) * 64, k0, fb, (uint16_t)0x3);
                } else if constexpr (VAR == 3) {
                    tma_load_2d(sA + stage * 16384, &tmA0, kt * 64, m0, fb);
#pragma unroll
                    for (int q = 0; q < 3; q++)
                        tma_load_2d(sB + stage * C::B_STAGE + q * 8192, &tmB0, nt * 176 + q * 64, kt * 64, fb);
                } else {
                    tma_load_2d_mc(sA + stage * 16384 + rank * 8192, &tmA0, kt * 64, m0 + rank * 64, fb, (uint16_t)0x3);
                    tma_load_2d(sB + stage * C::B_STAGE, &tmB0, nt * 64, kt * 64, fb);
                }
                if (++stage == STAGES) {
                    stage = 0;
                    phase ^= 1;
                }
            }
        }
    } else {
        const int wg = warp >> 2;
        pdl_wait();
        if constexpr (VAR == 1) {
            if (blockIdx.x == 0 && tid == 0) g_mod_cnt = 0u;
        }
        if constexpr (C::A_RES) {
            const __nv_bfloat16* src = (VAR == 1) ? xin : g_x1;
            const float* msh = g_mod + (VAR == 1 ? 0 : 3 * D_);
            const float* msc = g_mod + (VAR == 1 ? 1 * D_ : 4 * D_);
            float sh[16], sc[16];
#pragma unroll
            for (int bt = 0; bt < 2; bt++) {
                uint4 v[8][2];
#pragma unroll
                for (int r = 0; r < 8; r++) {
                    const __nv_bfloat16* row = src + (size_t)(m0 + warp * 16 + bt * 8 + r) * D_;
                    v[r][0] = *reinterpret_cast<const uint4*>(row + lane * 8);
                    v[r][1] = *reinterpret_cast<const uint4*>(row + 256 + lane * 8);
                }
                if (bt == 0) {
#pragma unroll
                    for (int j = 0; j < 8; j++) {
                        sh[j] = msh[lane * 8 + j];
                        sc[j] = 1.0f + msc[lane * 8 + j];
                        sh[8 + j] = msh[256 + lane * 8 + j];
                        sc[8 + j] = 1.0f + msc[256 + lane * 8 + j];
                    }
                }
#pragma unroll
                for (int r = 0; r < 8; r++) {
                    float f[16];
                    const __nv_bfloat162* p0 = reinterpret_cast<const __nv_bfloat162*>(&v[r][0]);
                    const __nv_bfloat162* p1 = reinterpret_cast<const __nv_bfloat162*>(&v[r][1]);
#pragma unroll
                    for (int j = 0; j < 4; j++) {
                        float2 a = __bfloat1622float2(p0[j]);
                        f[2 * j] = a.x;
                        f[2 * j + 1] = a.y;
                        float2 b = __bfloat1622float2(p1[j]);
                        f[8 + 2 * j] = b.x;
                        f[8 + 2 * j + 1] = b.y;
                    }
                    float s = 0.f;
#pragma unroll
                    for (int j = 0; j < 16; j++) s += f[j];
#pragma unroll
                    for (int o = 16; o > 0; o >>= 1) s += __shfl_xor_sync(0xffffffffu, s, o);
                    const float mean = s * (1.0f / D_);
                    float q = 0.f;
#pragma unroll
                    for (int j = 0; j < 16; j++) {
                        f[j] -= mean;
                        q += f[j] * f[j];
                    }
#pragma unroll
                    for (int o = 16; o > 0; o >>= 1) q += __shfl_xor_sync(0xffffffffu, q, o);
                    const float rstd = rsqrtf(q * (1.0f / D_) + 1e-5f);
                    uint4 o0, o1;
                    uint32_t* o0p = reinterpret_cast<uint32_t*>(&o0);
                    uint32_t* o1p = reinterpret_cast<uint32_t*>(&o1);
#pragma unroll
                    for (int j = 0; j < 4; j++) {
                        o0p[j] = pack_bf16(f[2 * j] * rstd * sc[2 * j] + sh[2 * j], f[2 * j + 1] * rstd * sc[2 * j + 1] + sh[2 * j + 1]);
                        o1p[j] = pack_bf16(f[8 + 2 * j] * rstd * sc[8 + 2 * j] + sh[8 + 2 * j],
                                           f[8 + 2 * j + 1] * rstd * sc[8 + 2 * j + 1] + sh[8 + 2 * j + 1]);
                    }
                    const int row = warp * 16 + bt * 8 + r;
                    const uint32_t chunk = (uint32_t)(lane & 7) ^ (uint32_t)(row & 7);
                    const uint32_t a0 = sA + (lane >> 3) * 16384 + row * 128 + chunk * 16;
                    const uint32_t a1 = a0 + 4 * 16384;
                    asm volatile("st.shared.v4.b32 [%0], {%1, %2, %3, %4};" ::"r"(a0), "r"(o0.x), "r"(o0.y), "r"(o0.z), "r"(o0.w) : "memory");
                    asm volatile("st.shared.v4.b32 [%0], {%1, %2, %3, %4};" ::"r"(a1), "r"(o1.x), "r"(o1.y), "r"(o1.z), "r"(o1.w) : "memory");
                }
            }
            fence_proxy_async();
            named_bar_sync(1, 256);
        }

        float acc[BN / 2];
        int stage = 0, phase = 0;
        for (int kt = 0; kt < KT; kt++) {
            mbar_wait(full0 + 8 * stage, phase);
            const uint32_t a_base = (C::A_RES ? sA + kt * 16384 : sA + stage * 16384) + wg * 8192;
            const uint32_t b_base = sB + stage * C::B_STAGE;
            wgmma_fence();
#pragma unroll
            for (int k = 0; k < 4; k++) {
                const uint64_t da = make_desc(a_base + k * 32, 16, 1024);
                uint64_t db;
                if constexpr (C::B_MN) db = make_desc(b_base + k * 2048, 8192, 1024);
                else db = make_desc(b_base + k * 32, 16, 1024);
                wgmma_bn<BN, C::B_MN ? 1 : 0>(acc, da, db, (kt | k) != 0);
            }
            wgmma_commit();
            if (kt > 0) {
                wgmma_wait<1>();
                const int ps = (stage == 0) ? STAGES - 1 : stage - 1;
                if constexpr (CL > 1) {
                    if ((tid & 127) < CL) mbar_arrive_remote(empty0 + 8 * ps, tid & 127);
                } else {
                    if ((tid & 127) == 0) mbar_arrive(empty0 + 8 * ps);
                }
            }
            if (++stage == STAGES) {
                stage = 0;
                phase ^= 1;
            }
        }
        wgmma_wait<0>();

        const int r0 = wg * 64 + (warp & 3) * 16 + (lane >> 2);
        const int cq = (lane & 3) * 2;
        {
            named_bar_sync(2, 256);
            const uint32_t stg = smem_base + wg * 32768;
            const int rl = (warp & 3) * 16 + (lane >> 2);
            if constexpr (VAR == 4) {
                const __nv_bfloat16* xr = g_x1 + (size_t)(m0 + r0) * D_ + nt * 64 + cq;
                const float* gb = g_mod + 5 * D_ + nt * 64 + cq;
#pragma unroll
                for (int j = 0; j < BN / 8; j++) {
                    float2 xa = __bfloat1622float2(*reinterpret_cast<const __nv_bfloat162*>(xr + j * 8));
                    float2 xb = __bfloat1622float2(*reinterpret_cast<const __nv_bfloat162*>(xr + 8 * D_ + j * 8));
                    float g0 = gb[j * 8], g1 = gb[j * 8 + 1];
                    acc[4 * j + 0] = xa.x + g0 * acc[4 * j + 0];
                    acc[4 * j + 1] = xa.y + g1 * acc[4 * j + 1];
                    acc[4 * j + 2] = xb.x + g0 * acc[4 * j + 2];
                    acc[4 * j + 3] = xb.y + g1 * acc[4 * j + 3];
                }
            }
#pragma unroll
            for (int j = 0; j < BN / 8; j++) {
                float v0 = acc[4 * j], v1 = acc[4 * j + 1], v2 = acc[4 * j + 2], v3 = acc[4 * j + 3];
                if constexpr (VAR == 3) {
                    v0 = fmaxf(v0, 0.f);
                    v1 = fmaxf(v1, 0.f);
                    v2 = fmaxf(v2, 0.f);
                    v3 = fmaxf(v3, 0.f);
                }
                const uint32_t sub = stg + (j >> 3) * 8192;
                const uint32_t ch = (uint32_t)(j & 7);
                const uint32_t ad0 = sub + rl * 128 + ((ch ^ (uint32_t)(rl & 7)) << 4) + cq * 2;
                const uint32_t ad1 = sub + (rl + 8) * 128 + ((ch ^ (uint32_t)((rl + 8) & 7)) << 4) + cq * 2;
                asm volatile("st.shared.b32 [%0], %1;" ::"r"(ad0), "r"(pack_bf16(v0, v1)) : "memory");
                asm volatile("st.shared.b32 [%0], %1;" ::"r"(ad1), "r"(pack_bf16(v2, v3)) : "memory");
            }
            named_bar_sync(3 + wg, 128);
            constexpr int NCH = BN / 8;
            const int t = tid & 127;
            for (int i = t; i < 64 * NCH; i += 128) {
                const int row = i / NCH, ch = i % NCH;
                const uint32_t ad = stg + (ch >> 3) * 8192 + row * 128 + ((((uint32_t)ch & 7) ^ (uint32_t)(row & 7)) << 4);
                uint4 val;
                asm volatile("ld.shared.v4.b32 {%0, %1, %2, %3}, [%4];" : "=r"(val.x), "=r"(val.y), "=r"(val.z), "=r"(val.w) : "r"(ad));
                const int grow = m0 + wg * 64 + row;
                if constexpr (VAR == 1) {
                    *reinterpret_cast<uint4*>(g_ab + (size_t)grow * 1024 + nt * 128 + ch * 8) = val;
                } else if constexpr (VAR == 2) {
                    *reinterpret_cast<uint4*>(g_part + (size_t)kq * S_ * D_ + (size_t)grow * D_ + nt * 256 + ch * 8) = val;
                } else if constexpr (VAR == 3) {
                    const int gc = nt * 176 + ch * 8;
                    if (gc < DFF_) *reinterpret_cast<uint4*>(g_h1 + (size_t)grow * DFF_ + gc) = val;
                } else {
                    *reinterpret_cast<uint4*>(out + (size_t)grow * D_ + nt * 64 + ch * 8) = val;
                }
            }
        }
    }
    if constexpr (VAR == 2) {
        if (warp < 8) {
            __threadfence();
            named_bar_sync(5, 256);
            if (tid == 0) atomicAdd(&g_rb_cnt[mt], 1u);
            if (tid == 0) {
                volatile unsigned int* cnt = &g_rb_cnt[mt];
                int it = 0;
                while (*cnt < 8u) {
                    __nanosleep(32);
                    if (++it > (1 << 22)) __trap();
                }
                __threadfence();
            }
            named_bar_sync(6, 256);
            const int sub = kq * 2 + nt;
            uint4 xv[2][2], pq[2][4][2];
#pragma unroll
            for (int rr = 0; rr < 2; rr++) {
                const size_t base = (size_t)(m0 + sub * 16 + warp * 2 + rr) * D_;
#pragma unroll
                for (int h = 0; h < 2; h++) {
                    xv[rr][h] = *reinterpret_cast<const uint4*>(xin + base + h * 256 + lane * 8);
#pragma unroll
                    for (int q = 0; q < 4; q++)
                        pq[rr][q][h] = __ldcg(reinterpret_cast<const uint4*>(g_part + (size_t)q * S_ * D_ + base + h * 256 + lane * 8));
                }
            }
            float ga[16], sh[16], sc[16];
#pragma unroll
            for (int h = 0; h < 2; h++) {
#pragma unroll
                for (int v = 0; v < 2; v++) {
                    const float4 g4 = *reinterpret_cast<const float4*>(g_mod + 2 * D_ + h * 256 + lane * 8 + v * 4);
                    const float4 s4 = *reinterpret_cast<const float4*>(g_mod + 3 * D_ + h * 256 + lane * 8 + v * 4);
                    const float4 c4 = *reinterpret_cast<const float4*>(g_mod + 4 * D_ + h * 256 + lane * 8 + v * 4);
                    const int o = h * 8 + v * 4;
                    ga[o] = g4.x; ga[o + 1] = g4.y; ga[o + 2] = g4.z; ga[o + 3] = g4.w;
                    sh[o] = s4.x; sh[o + 1] = s4.y; sh[o + 2] = s4.z; sh[o + 3] = s4.w;
                    sc[o] = 1.0f + c4.x; sc[o + 1] = 1.0f + c4.y; sc[o + 2] = 1.0f + c4.z; sc[o + 3] = 1.0f + c4.w;
                }
            }
#pragma unroll
            for (int rr = 0; rr < 2; rr++) {
                const size_t base = (size_t)(m0 + sub * 16 + warp * 2 + rr) * D_;
                float f[16];
#pragma unroll
                for (int h = 0; h < 2; h++) {
#pragma unroll
                    for (int j = 0; j < 4; j++) {
                        float2 a0 = __bfloat1622float2(reinterpret_cast<const __nv_bfloat162*>(&pq[rr][0][h])[j]);
                        float2 a1 = __bfloat1622float2(reinterpret_cast<const __nv_bfloat162*>(&pq[rr][1][h])[j]);
                        float2 a2 = __bfloat1622float2(reinterpret_cast<const __nv_bfloat162*>(&pq[rr][2][h])[j]);
                        float2 a3 = __bfloat1622float2(reinterpret_cast<const __nv_bfloat162*>(&pq[rr][3][h])[j]);
                        float2 xx = __bfloat1622float2(reinterpret_cast<const __nv_bfloat162*>(&xv[rr][h])[j]);
                        const int o = h * 8 + 2 * j;
                        f[o] = __bfloat162float(__float2bfloat16(xx.x + ga[o] * ((a0.x + a1.x) - (a2.x + a3.x))));
                        f[o + 1] = __bfloat162float(__float2bfloat16(xx.y + ga[o + 1] * ((a0.y + a1.y) - (a2.y + a3.y))));
                    }
                }
                *reinterpret_cast<uint4*>(g_x1 + base + lane * 8) =
                    make_uint4(pack_bf16(f[0], f[1]), pack_bf16(f[2], f[3]), pack_bf16(f[4], f[5]), pack_bf16(f[6], f[7]));
                *reinterpret_cast<uint4*>(g_x1 + base + 256 + lane * 8) =
                    make_uint4(pack_bf16(f[8], f[9]), pack_bf16(f[10], f[11]), pack_bf16(f[12], f[13]), pack_bf16(f[14], f[15]));
                float sm = 0.f;
#pragma unroll
                for (int j = 0; j < 16; j++) sm += f[j];
#pragma unroll
                for (int o = 16; o > 0; o >>= 1) sm += __shfl_xor_sync(0xffffffffu, sm, o);
                const float mean = sm * (1.0f / D_);
                float qq = 0.f;
#pragma unroll
                for (int j = 0; j < 16; j++) { f[j] -= mean; qq += f[j] * f[j]; }
#pragma unroll
                for (int o = 16; o > 0; o >>= 1) qq += __shfl_xor_sync(0xffffffffu, qq, o);
                const float rstd = rsqrtf(qq * (1.0f / D_) + 1e-5f);
                uint32_t o[8];
#pragma unroll
                for (int j = 0; j < 8; j++)
                    o[j] = pack_bf16(f[2 * j] * rstd * sc[2 * j] + sh[2 * j], f[2 * j + 1] * rstd * sc[2 * j + 1] + sh[2 * j + 1]);
                *reinterpret_cast<uint4*>(g_h2 + base + lane * 8) = make_uint4(o[0], o[1], o[2], o[3]);
                *reinterpret_cast<uint4*>(g_h2 + base + 256 + lane * 8) = make_uint4(o[4], o[5], o[6], o[7]);
            }
        }
    }
    if constexpr (VAR == 3) {
        if (blockIdx.x < 16 && threadIdx.x == 0) g_rb_cnt[blockIdx.x] = 0u;
    }
    if constexpr (CL > 1) cluster_sync();
}

typedef CUresult (*EncodeFn)(CUtensorMap*, CUtensorMapDataType, cuuint32_t, void*, const cuuint64_t*, const cuuint64_t*,
                             const cuuint32_t*, const cuuint32_t*, CUtensorMapInterleave, CUtensorMapSwizzle,
                             CUtensorMapL2promotion, CUtensorMapFloatOOBfill);

void make_map(EncodeFn fn, CUtensorMap* m, const void* ptr, uint64_t inner, uint64_t outer, uint64_t pitch_bytes,
              uint32_t box_inner, uint32_t box_outer) {
    cuuint64_t dims[2] = {inner, outer};
    cuuint64_t strides[1] = {pitch_bytes};
    cuuint32_t box[2] = {box_inner, box_outer};
    cuuint32_t estr[2] = {1, 1};
    fn(m, CU_TENSOR_MAP_DATA_TYPE_BFLOAT16, 2, const_cast<void*>(ptr), dims, strides, box, estr,
       CU_TENSOR_MAP_INTERLEAVE_NONE, CU_TENSOR_MAP_SWIZZLE_128B, CU_TENSOR_MAP_L2_PROMOTION_L2_256B,
       CU_TENSOR_MAP_FLOAT_OOB_FILL_NONE);
}

template <int VAR>
void launch_gemm(int grid, const CUtensorMap& a0, const CUtensorMap& a1, const CUtensorMap& b0, const CUtensorMap& b1,
                 const __nv_bfloat16* xin, __nv_bfloat16* out, cudaStream_t st) {
    cudaLaunchConfig_t cfg = {};
    cfg.gridDim = dim3(grid);
    cfg.blockDim = dim3(288);
    cfg.dynamicSmemBytes = smem_bytes<VAR>();
    cfg.stream = st;
    cudaLaunchAttribute attr[2];
    attr[0].id = cudaLaunchAttributeClusterDimension;
    attr[0].val.clusterDim.x = Cfg<VAR>::CL;
    attr[0].val.clusterDim.y = 1;
    attr[0].val.clusterDim.z = 1;
    attr[1].id = cudaLaunchAttributeProgrammaticStreamSerialization;
    attr[1].val.programmaticStreamSerializationAllowed = 1;
    cfg.attrs = attr;
    cfg.numAttrs = 2;
    cudaLaunchKernelEx(&cfg, gemm_kernel<VAR>, a0, a1, b0, b1, xin, out);
}

template <int LNV>
void launch_ln(const __nv_bfloat16* x, const __nv_bfloat16* c, const __nv_bfloat16* w_mod, cudaStream_t st) {
    cudaLaunchConfig_t cfg = {};
    cfg.gridDim = dim3(S_ / 8);
    cfg.blockDim = dim3(256);
    cfg.stream = st;
    cudaLaunchAttribute attr[1];
    attr[0].id = cudaLaunchAttributeProgrammaticStreamSerialization;
    attr[0].val.programmaticStreamSerializationAllowed = 1;
    cfg.attrs = attr;
    cfg.numAttrs = PDL_LN;
    cudaLaunchKernelEx(&cfg, combine_kernel<LNV>, x, c, w_mod);
}

}

extern "C" void kernel_launch(void* const* d_in, const int* in_sizes, int n_in, void* d_out, int out_size) {
    const __nv_bfloat16* x = (const __nv_bfloat16*)d_in[0];
    const __nv_bfloat16* ws_re = (const __nv_bfloat16*)d_in[1];
    const __nv_bfloat16* ws_im = (const __nv_bfloat16*)d_in[2];
    const __nv_bfloat16* wd_re = (const __nv_bfloat16*)d_in[3];
    const __nv_bfloat16* wd_im = (const __nv_bfloat16*)d_in[4];
    const __nv_bfloat16* w1 = (const __nv_bfloat16*)d_in[6];
    const __nv_bfloat16* w2 = (const __nv_bfloat16*)d_in[7];
    const __nv_bfloat16* c = (const __nv_bfloat16*)d_in[8];
    const __nv_bfloat16* w_mod = (const __nv_bfloat16*)d_in[9];
    __nv_bfloat16* out = (__nv_bfloat16*)d_out;
    cudaStream_t st = cudaStreamPerThread;

    static EncodeFn enc = nullptr;
    static bool attr_done = false;
    if (!enc) {
        void* fn = nullptr;
        cudaDriverEntryPointQueryResult qres;
        cudaGetDriverEntryPoint("cuTensorMapEncodeTiled", &fn, cudaEnableDefault, &qres);
        enc = (EncodeFn)fn;
    }
    if (!attr_done) {
        cudaFuncSetAttribute(gemm_kernel<1>, cudaFuncAttributeMaxDynamicSharedMemorySize, smem_bytes<1>());
        cudaFuncSetAttribute(gemm_kernel<2>, cudaFuncAttributeMaxDynamicSharedMemorySize, smem_bytes<2>());
        cudaFuncSetAttribute(gemm_kernel<3>, cudaFuncAttributeMaxDynamicSharedMemorySize, smem_bytes<3>());
        cudaFuncSetAttribute(gemm_kernel<4>, cudaFuncAttributeMaxDynamicSharedMemorySize, smem_bytes<4>());
        attr_done = true;
    }
    void *p_ab, *p_h1, *p_h2;
    cudaGetSymbolAddress(&p_h2, g_h2);
    cudaGetSymbolAddress(&p_ab, g_ab);
    cudaGetSymbolAddress(&p_h1, g_h1);

    CUtensorMap tm_h2, tm_wdre, tm_wdim, tm_wsre, tm_wsim, tm_ab, tm_w1, tm_h1, tm_w2;
    make_map(enc, &tm_wdre, wd_re, D_, D_, D_ * 2, 64, 128);
    make_map(enc, &tm_wdim, wd_im, D_, D_, D_ * 2, 64, 128);
    make_map(enc, &tm_wsre, ws_re, S_, S_, S_ * 2, 64, 128);
    make_map(enc, &tm_wsim, ws_im, S_, S_, S_ * 2, 64, 128);
    make_map(enc, &tm_ab, p_ab, 1024, S_, 1024 * 2, 64, 64);
    make_map(enc, &tm_h2, p_h2, D_, S_, D_ * 2, 64, 128);
    make_map(enc, &tm_w1, w1, DFF_, D_, DFF_ * 2, 64, 64);
    make_map(enc, &tm_h1, p_h1, DFF_, S_, DFF_ * 2, 64, 64);
    make_map(enc, &tm_w2, w2, D_, DFF_, D_ * 2, 64, 64);

    launch_ln<1>(x, c, w_mod, st);
    launch_gemm<1>(128, tm_h2, tm_h2, tm_wdre, tm_wdim, x, nullptr, st);
    launch_gemm<2>(128, tm_wsre, tm_wsim, tm_ab, tm_ab, x, nullptr, st);
    launch_gemm<3>(128, tm_h2, tm_h2, tm_w1, tm_w1, nullptr, nullptr, st);
    launch_gemm<4>(128, tm_h1, tm_h1, tm_w2, tm_w2, nullptr, out, st);
}
```
